```python
import torch

def _softmax(x, axis=-1):
    return torch.softmax(x, dim=axis)

def _gelu(x):
    return torch.nn.functional.gelu(x, approximate='tanh')

def _silu(x):
    return torch.nn.functional.silu(x)

def _sigmoid(x):
    return torch.sigmoid(x)

def _layernorm(x, axis=-1, eps=1e-05):
    m = x.mean(dim=axis, keepdim=True)
    v = x.var(dim=axis, keepdim=True, unbiased=False)
    return (x - m) / torch.sqrt(v + eps)

def _scatter_add(tgt, idx, src, axis=0):
    return tgt.clone().index_add_(axis, idx, src)

def _segment_sum(src, seg, n):
    out = torch.zeros((n,) + src.shape[1:], dtype=src.dtype)
    return out.index_add_(0, seg, src)

def _pad(x, pw):
    flat = tuple((v for pair in reversed(pw) for v in pair))
    return torch.nn.functional.pad(x, flat)
kernel_name = 'standalone__kv_cache_quant_pre_rope_vs_post_rope__decode'

def setup_inputs():

    _w = lambda a: (lambda t: t.to(torch.bfloat16) if t.is_floating_point() else t)(torch.as_tensor(a))
    B, Sq, Skv = (1, 1, 16384)
    H, Dh0 = (32, 192)
    G = -1 if -1 > 0 else Dh0
    G = max(2, G // 2 * 2)
    Dh = max(G, Dh0 // G * G)
    Skv = max(Skv, Sq)
    ng = Dh // G
    bits = 3 if 3 > 1 else 4
    bits = max(2, min(8, bits))
    qmax = (1 << bits) - 1
    half = Dh // 2
    inv = 1.0 / 10000.0 ** (torch.arange(half) / max(1, half))
    ang_k = torch.arange(Skv)[:, None] * inv[None, :]
    ang_q = torch.arange(Skv - Sq, Skv)[:, None] * inv[None, :]
    kc = torch.cat([torch.cos(ang_k), torch.cos(ang_k)], dim=-1)
    ks = torch.cat([torch.sin(ang_k), torch.sin(ang_k)], dim=-1)
    qc = torch.cat([torch.cos(ang_q), torch.cos(ang_q)], dim=-1)
    qs = torch.cat([torch.sin(ang_q), torch.sin(ang_q)], dim=-1)
    qk_i = torch.randint(0, qmax + 1, (B, H, Skv, Dh)).to(torch.int32)
    qv_i = torch.randint(0, qmax + 1, (B, H, Skv, Dh)).to(torch.int32)
    ksc = torch.abs((lambda *s: torch.randn(*s, dtype=torch.bfloat16) * 0.4)(B, H, Skv, ng)) * 0.1 + 0.01
    kzp = torch.full((B, H, Skv, ng), qmax / 2.0)
    vsc = torch.abs((lambda *s: torch.randn(*s, dtype=torch.bfloat16) * 0.4)(B, H, Skv, ng)) * 0.1 + 0.01
    vzp = torch.full((B, H, Skv, ng), qmax / 2.0)
    return {'q': _w((lambda *s: torch.randn(*s, dtype=torch.bfloat16) * 6.4)(B, H, Sq, Dh) * 0.5), 'qk': _w(qk_i), 'k_scales': _w(ksc), 'k_zeros': _w(kzp), 'qv': _w(qv_i), 'v_scales': _w(vsc), 'v_zeros': _w(vzp), 'q_cos': _w(qc), 'q_sin': _w(qs), 'k_cos': _w(kc), 'k_sin': _w(ks)}

def reference(q, qk, k_scales, k_zeros, qv, v_scales, v_zeros, q_cos, q_sin, k_cos, k_sin):
    B, H, Sq, Dh = q.shape
    ng = k_scales.shape[-1]
    G = Dh // ng
    half = Dh // 2
    ks = (lambda x, n, axis: torch.repeat_interleave(x, n, dim=axis))(k_scales, G, axis=-1)
    kz = (lambda x, n, axis: torch.repeat_interleave(x, n, dim=axis))(k_zeros, G, axis=-1)
    k = ((lambda x, dt: x.to(dt))(qk, q.dtype) - kz) * ks
    vs = (lambda x, n, axis: torch.repeat_interleave(x, n, dim=axis))(v_scales, G, axis=-1)
    vz = (lambda x, n, axis: torch.repeat_interleave(x, n, dim=axis))(v_zeros, G, axis=-1)
    v = ((lambda x, dt: x.to(dt))(qv, q.dtype) - vz) * vs
    k1 = k[..., :half].clone()
    k2 = k[..., half:].clone()
    krh = torch.concatenate([-k2, k1], axis=-1)
    kr = k * k_cos[None, None, :, :] + krh * k_sin[None, None, :, :]
    q1 = q[..., :half].clone()
    q2 = q[..., half:].clone()
    qrh = torch.concatenate([-q2, q1], axis=-1)
    qr = q * q_cos[None, None, :, :] + qrh * q_sin[None, None, :, :]
    logits = torch.einsum('bhqd,bhkd->bhqk', qr, kr) * float(Dh) ** (-0.5)
    attn = _softmax(logits, axis=-1)
    out = torch.einsum('bhqk,bhkd->bhqd', attn, v)
    return out
```

```cpp
#include <cuda_runtime.h>
#include <cuda.h>
#include <cuda_bf16.h>
#include <stdint.h>

namespace {

constexpr int H = 32;
constexpr int S = 16384;
constexpr int D = 192;
constexpr int NCTA = 128;
constexpr int POS = S / NCTA;
constexpr int NBLK = S / POS;
constexpr int SROWS = 64;
constexpr int ROWB = D * 4;
constexpr int DATA_B = SROWS * ROWB;
constexpr int HALF_B = DATA_B / 2;
constexpr int AUX_SCALE = DATA_B;
constexpr int AUX_ZERO = AUX_SCALE + SROWS * 2;
constexpr int AUX_LOGIT = AUX_ZERO + SROWS * 2;
constexpr int AUX_ITEM = AUX_LOGIT + SROWS * 4;
constexpr int STAGE_B = AUX_ITEM + 128;
constexpr int NST = 4;
constexpr int KSTAGES = 2 * H;

constexpr int PROWS = 384;
constexpr int NSL = 3;
constexpr int PCOLS = D / NSL;
constexpr int PBOX = 48;
constexpr int PU = PBOX / 12;
constexpr int PREG = 2;
constexpr int PSUB = PROWS / PBOX - PREG;
constexpr int PEARLY = 2;
constexpr int PBOX_B = PBOX * PCOLS * 4;
constexpr int BPS = DATA_B / PBOX_B;
constexpr int PFIRST = 95, PSTEP = 25;

constexpr int BIG = 10, NB = 21, N4 = 5, N1 = 12;
constexpr int N2 = ((S - PROWS) / SROWS - BIG * NB - 4 * N4 - N1) / 2;
constexpr int NPART = NB + N4 + N2 + N1;
constexpr int NE = NPART - 8;
constexpr int ALL_ITEMS = NPART * H;
constexpr int PART_V = PCOLS / 4;
constexpr int SLICE_V = (NPART + 1) * PART_V;
constexpr uint32_t ITEM_END = 1u << 31;
static_assert(N2 > 0 && BIG * NB + 4 * N4 + 2 * N2 + N1 == (S - PROWS) / SROWS && BIG < 16, "item classes");

constexpr int GH = 8;
constexpr int NG = H / GH;
constexpr int KW = 8;
constexpr int VW = 6;
constexpr int PRODUCER = KW + VW;
constexpr int NTHREADS = 512;

constexpr int OFF_QR = NST * STAGE_B;
constexpr int OFF_PV = OFF_QR + H * D * 2;
constexpr int OFF_QRAW = OFF_PV + VW * SROWS * 8;
constexpr int QRAW_B = H * D * 2 + 2 * D * 2;
constexpr int OFF_PW = OFF_QRAW;
constexpr int OFF_RED = OFF_PW + PROWS * 8;
constexpr int OFF_PRE = OFF_RED + 192 * 16;
constexpr int OFF_PL = OFF_PRE + 7 * 256;
constexpr int OFF_HKEY = OFF_QRAW + QRAW_B;
constexpr int OFF_HMAX = OFF_HKEY + H * 4;
constexpr int OFF_KPROG = OFF_HMAX + H * 4;
constexpr int OFF_READY = OFF_KPROG + 32;
constexpr int OFF_BAR = OFF_READY + 16;
constexpr int SMEM_B = OFF_BAR + (31 + PSUB) * 8;
static_assert(OFF_PL + 16 <= OFF_HKEY && PSUB <= 2 * BPS && PEARLY + PREG - 1 <= PSUB, "private rows");
static_assert(PBOX % 12 == 0 && PROWS % PBOX == 0 && PROWS % POS == 0 && PART_V == 16 && NPART <= PCOLS, "private rows");
static_assert(SMEM_B <= 232448, "shared memory budget");
static_assert(STAGE_B % 128 == 0, "stage alignment");
static_assert(NCTA == (NSL + 1) * H, "owners of the output slices");
static_assert(NCTA == NBLK, "one position block per CTA in the K phase");
static_assert((NCTA & (NCTA - 1)) == 0, "progress counter windows");
static_assert(POS * D * 2 == DATA_B, "cos/sin tiles are staged through ring slots");

constexpr unsigned SPIN_LIMIT = 1u << 23;

__device__ __align__(256) float g_logits[H * S];
__device__ __align__(256) uint4 g_part[H * NSL * SLICE_V];
__device__ __align__(128) unsigned g_key[2 * H];
__device__ __align__(128) unsigned g_kcnt[NG];
__device__ __align__(128) unsigned g_queue;

__device__ __forceinline__ uint32_t smem_u32(const void* p) { return (uint32_t)__cvta_generic_to_shared(p); }
__device__ __forceinline__ void mbar_init(uint32_t bar, uint32_t cnt) {
    asm volatile("mbarrier.init.shared::cta.b64 [%0], %1;" ::"r"(bar), "r"(cnt) : "memory");
}
__device__ __forceinline__ void mbar_expect_tx(uint32_t bar, uint32_t bytes) {
    asm volatile("mbarrier.arrive.expect_tx.shared::cta.b64 _, [%0], %1;" ::"r"(bar), "r"(bytes) : "memory");
}
__device__ __forceinline__ void mbar_arrive(uint32_t bar) {
    asm volatile("mbarrier.arrive.shared::cta.b64 _, [%0];" ::"r"(bar) : "memory");
}
__device__ __forceinline__ void mbar_wait(uint32_t bar, uint32_t parity) {
    uint32_t done;
    unsigned spins = 0;
    do {
        asm volatile(
            "{\n.reg .pred p;\n"
            "mbarrier.try_wait.parity.shared::cta.b64 p, [%1], %2;\n"
            "selp.u32 %0, 1, 0, p;\n}"
            : "=r"(done)
            : "r"(bar), "r"(parity)
            : "memory");
        if (++spins > SPIN_LIMIT) __trap();
    } while (!done);
}
__device__ __forceinline__ void bulk_g2s(uint32_t dst, const void* src, uint32_t bytes, uint32_t bar, uint64_t pol) {
    asm volatile(
        "cp.async.bulk.shared::cluster.global.mbarrier::complete_tx::bytes.L2::cache_hint [%0], [%1], %2, [%3], %4;"
        ::"r"(dst), "l"(src), "r"(bytes), "r"(bar), "l"(pol)
        : "memory");
}
__device__ __forceinline__ void bulk_g2s_nohint(uint32_t dst, const void* src, uint32_t bytes, uint32_t bar) {
    asm volatile("cp.async.bulk.shared::cluster.global.mbarrier::complete_tx::bytes [%0], [%1], %2, [%3];"
                 ::"r"(dst), "l"(src), "r"(bytes), "r"(bar)
                 : "memory");
}
__device__ __forceinline__ void box_g2s(uint32_t dst, const CUtensorMap* map, int col, int row, uint32_t bar, uint64_t pol) {
    asm volatile(
        "cp.async.bulk.tensor.2d.shared::cluster.global.mbarrier::complete_tx::bytes.L2::cache_hint [%0], [%1, {%2, %3}], [%4], %5;"
        ::"r"(dst), "l"(map), "r"(col), "r"(row), "r"(bar), "l"(pol)
        : "memory");
}
__device__ __forceinline__ void st_relaxed(uint4* p, uint4 v) {
    asm volatile("st.relaxed.gpu.global.v4.u32 [%0], {%1, %2, %3, %4};" ::"l"(p), "r"(v.x), "r"(v.y), "r"(v.z), "r"(v.w) : "memory");
}
__device__ __forceinline__ void ld_relaxed_if(uint4& r, const uint4* p, bool cond) {
    asm volatile("{\n.reg .pred p;\nsetp.ne.u32 p, %5, 0;\n@p ld.relaxed.gpu.global.v4.u32 {%0, %1, %2, %3}, [%4];\n}"
                 : "+r"(r.x), "+r"(r.y), "+r"(r.z), "+r"(r.w) : "l"(p), "r"((unsigned)cond) : "memory");
}
__device__ __forceinline__ unsigned ld_acquire_cta(uint32_t addr) {
    unsigned v;
    asm volatile("ld.acquire.cta.shared.u32 %0, [%1];" : "=r"(v) : "r"(addr) : "memory");
    return v;
}
__device__ __forceinline__ uint32_t float_key(float x) {
    const uint32_t u = __float_as_uint(x);
    return u ^ ((uint32_t)((int32_t)u >> 31) | 0x80000000u);
}
__device__ __forceinline__ float key_float(uint32_t k) {
    return __uint_as_float(k ^ ((uint32_t)((int32_t)~k >> 31) | 0x80000000u));
}
template <int N>
__device__ __forceinline__ float4 collect(const uint4* base, int stride, int first, int count, int lane, unsigned pause) {
    uint4 r[N];
#pragma unroll
    for (int i = 0; i < N; i++) {
        const uint32_t init = first + i * stride < count ? 0u : 1u;
        r[i] = make_uint4(init, init, init, init);
    }
    for (unsigned spins = 0;; spins++) {
#pragma unroll
        for (int i = 0; i < N; i++)
            ld_relaxed_if(r[i], base + (first + i * stride) * PART_V + (lane & 15), !(r[i].x & r[i].y & r[i].z & r[i].w & 1));
        uint32_t ok = 1;
#pragma unroll
        for (int i = 0; i < N; i++) ok &= r[i].x & r[i].y & r[i].z & r[i].w;
        if (__all_sync(0xffffffffu, ok & 1)) break;
        if (spins > SPIN_LIMIT) __trap();
        if (pause) __nanosleep(pause);
    }
    float4 sum = make_float4(0.f, 0.f, 0.f, 0.f);
#pragma unroll
    for (int i = 0; i < N; i++) {
        sum.x += __uint_as_float(r[i].x & ~1u); sum.y += __uint_as_float(r[i].y & ~1u);
        sum.z += __uint_as_float(r[i].z & ~1u); sum.w += __uint_as_float(r[i].w & ~1u);
    }
    sum.x += __shfl_xor_sync(0xffffffffu, sum.x, 16); sum.y += __shfl_xor_sync(0xffffffffu, sum.y, 16);
    sum.z += __shfl_xor_sync(0xffffffffu, sum.z, 16); sum.w += __shfl_xor_sync(0xffffffffu, sum.w, 16);
    return sum;
}
__device__ __forceinline__ unsigned ld_acquire_gpu(const unsigned* p) {
    unsigned v;
    asm volatile("ld.acquire.gpu.global.u32 %0, [%1];" : "=r"(v) : "l"(p) : "memory");
    return v;
}
__device__ __forceinline__ uint4 lds128(uint32_t addr) {
    uint4 v;
    asm volatile("ld.shared.v4.u32 {%0,%1,%2,%3}, [%4];" : "=r"(v.x), "=r"(v.y), "=r"(v.z), "=r"(v.w) : "r"(addr));
    return v;
}
__device__ __forceinline__ uint2 lds64(uint32_t addr) {
    uint2 v;
    asm volatile("ld.shared.v2.u32 {%0,%1}, [%2];" : "=r"(v.x), "=r"(v.y) : "r"(addr));
    return v;
}
__device__ __forceinline__ uint32_t lds32(uint32_t addr) {
    uint32_t v;
    asm volatile("ld.shared.u32 %0, [%1];" : "=r"(v) : "r"(addr));
    return v;
}
__device__ __forceinline__ float lds_bf16(uint32_t addr) {
    unsigned short v;
    asm volatile("ld.shared.u16 %0, [%1];" : "=h"(v) : "r"(addr));
    return __uint_as_float((uint32_t)v << 16);
}
__device__ __forceinline__ float bf_lo(uint32_t x) { return __uint_as_float(x << 16); }
__device__ __forceinline__ float bf_hi(uint32_t x) { return __uint_as_float(x & 0xffff0000u); }
__device__ __forceinline__ float bf_round(float x) { return __bfloat162float(__float2bfloat16_rn(x)); }
__device__ __forceinline__ float ex2(float x) {
    float y;
    asm("ex2.approx.ftz.f32 %0, %1;" : "=f"(y) : "f"(x));
    return y;
}
__device__ __forceinline__ uint32_t clock32() {
    uint32_t c;
    asm volatile("mov.u32 %0, %clock;" : "=r"(c) :: "memory");
    return c;
}
__device__ __forceinline__ uint32_t clock32_after(uint32_t x) {
    uint32_t c;
    asm volatile("{\n.reg .pred p;\nsetp.eq.u32 p, %1, 0xffffffff;\n@p mov.u32 %0, %clock_hi;\n@!p mov.u32 %0, %clock;\n}"
                 : "=r"(c) : "r"(x) : "memory");
    return c;
}
__device__ __forceinline__ void named_bar(int id, int nthreads) {
    asm volatile("bar.sync %0, %1;" ::"r"(id), "r"(nthreads) : "memory");
}

__device__ __forceinline__ void issue_aux(uint32_t dst, uint32_t bar, size_t row0, const __nv_bfloat16* scales,
                                          const __nv_bfloat16* zeros, uint64_t pol) {
    bulk_g2s(dst + AUX_SCALE, scales + row0, SROWS * 2, bar, pol);
    bulk_g2s(dst + AUX_ZERO, zeros + row0, SROWS * 2, bar, pol);
}

__global__ void __launch_bounds__(NTHREADS, 1)
kv_decode_kernel(const __nv_bfloat16* __restrict__ k_cos, const __nv_bfloat16* __restrict__ k_sin,
                 const __nv_bfloat16* __restrict__ q, const int* __restrict__ qk,
                 const __nv_bfloat16* __restrict__ k_scales, const __nv_bfloat16* __restrict__ k_zeros,
                 const int* __restrict__ qv, const __nv_bfloat16* __restrict__ v_scales,
                 const __nv_bfloat16* __restrict__ v_zeros, const __nv_bfloat16* __restrict__ q_cos,
                 const __nv_bfloat16* __restrict__ q_sin, __nv_bfloat16* __restrict__ out,
                 const __grid_constant__ CUtensorMap v_map) {
    asm volatile("{\n.reg .pred p;\n.reg .u64 a;\n.reg .u32 t, c;\nmov.u32 t, %tid.x;\nmov.u32 c, %ctaid.x;\n"
                 "mad.wide.u32 a, c, %1, %0;\nmad.wide.u32 a, t, 128, a;\nsetp.lt.u32 p, t, 256;\n"
                 "@p prefetch.global.L2 [a];\n}"
                 ::"l"(k_cos), "n"(DATA_B) : "memory");
    extern __shared__ __align__(128) unsigned char smem[];
    const uint32_t sbase = smem_u32(smem);
    const uint32_t bar_full = sbase + OFF_BAR;
    const uint32_t bar_fullv = bar_full + 8 * 8;
    const uint32_t bar_auxv = bar_fullv + 8 * 8;
    const uint32_t bar_emptyk = bar_auxv + 4 * 8;
    const uint32_t bar_emptyv = bar_emptyk + 4 * 8;
    const uint32_t bar_qfull = bar_emptyv + 4 * 8;
    const uint32_t bar_near = bar_qfull + 8;
    const uint32_t bar_end = bar_near + 8;
    const uint32_t bar_priv = bar_end + 8;

    const int warp = threadIdx.x >> 5;
    const int lane = threadIdx.x & 31;
    const int b = blockIdx.x;
    const int hb = b >> 2, sl = b & 3;

    uint64_t pol = 0;
    if (threadIdx.x == PRODUCER * 32) {
        asm volatile("createpolicy.fractional.L2::evict_first.b64 %0, 1.0;" : "=l"(pol));
        const size_t row0 = (size_t)b * POS;
        mbar_init(bar_full + 8 * 4, 1);
        mbar_init(bar_full + 8 * 5, 1);
        asm volatile("fence.proxy.async.shared::cta;" ::: "memory");
#pragma unroll
        for (int p = 0; p < 2; p++) {
            mbar_expect_tx(bar_full + 8 * (4 + p), HALF_B);
            bulk_g2s(sbase + 2 * STAGE_B + p * HALF_B, k_cos + (row0 + p * (POS / 2)) * D, HALF_B, bar_full + 8 * (4 + p), pol);
        }
#pragma unroll
        for (int p = 0; p < 2; p++) {
            mbar_init(bar_full + 8 * (6 + p), 1);
            mbar_init(bar_full + 8 * p, 1);
            mbar_init(bar_full + 8 * (2 + p), 1);
        }
        mbar_init(bar_qfull, 1);
        asm volatile("fence.proxy.async.shared::cta;" ::: "memory");
#pragma unroll
        for (int p = 0; p < 2; p++) {
            mbar_expect_tx(bar_full + 8 * (6 + p), HALF_B);
            bulk_g2s(sbase + 3 * STAGE_B + p * HALF_B, k_sin + (row0 + p * (POS / 2)) * D, HALF_B, bar_full + 8 * (6 + p), pol);
        }
        mbar_expect_tx(bar_qfull, QRAW_B);
        bulk_g2s_nohint(sbase + OFF_QRAW, q, H * D * 2, bar_qfull);
        bulk_g2s_nohint(sbase + OFF_QRAW + H * D * 2, q_cos, D * 2, bar_qfull);
        bulk_g2s_nohint(sbase + OFF_QRAW + H * D * 2 + D * 2, q_sin, D * 2, bar_qfull);
        mbar_expect_tx(bar_full, HALF_B + 2 * SROWS * 2);
        bulk_g2s(sbase, qk + row0 * D, HALF_B, bar_full, pol);
        issue_aux(sbase, bar_full, row0, k_scales, k_zeros, pol);
        for (int s = 0; s < NST; s++) {
            mbar_init(bar_fullv + 16 * s, 1);
            mbar_init(bar_fullv + 16 * s + 8, 1);
            mbar_init(bar_auxv + 8 * s, 1);
            mbar_init(bar_emptyk + 8 * s, KW);
            mbar_init(bar_emptyv + 8 * s, VW);
        }
        mbar_init(bar_near, 1);
        mbar_init(bar_end, 1);
        for (int i = 0; i < PSUB; i++) {
            mbar_init(bar_priv + 8 * i, 1);
            mbar_expect_tx(bar_priv + 8 * i, PBOX_B);
        }
    }
    if (threadIdx.x < (OFF_BAR - OFF_HKEY) / 4)
        asm volatile("st.shared.u32 [%0], %1;" ::"r"(sbase + OFF_HKEY + 4 * threadIdx.x), "r"(0) : "memory");
    __syncthreads();

    if (warp < KW) {
        asm volatile("setmaxnreg.inc.sync.aligned.u32 168;");
        const int g = lane >> 3, j = lane & 7;

        uint2 cr[4][6], sr[4][6];
#pragma unroll
        for (int p = 4; p < 8; p++) mbar_wait(bar_full + 8 * p, 0);
#pragma unroll
        for (int P = 0; P < 4; P++) {
            const int row = SROWS * (P >> 1) + 8 * warp + 4 * (P & 1) + g;
#pragma unroll
            for (int c = 0; c < 6; c++) {
                cr[P][c] = lds64(sbase + 2 * STAGE_B + row * (D * 2) + (j + 8 * c) * 8);
                sr[P][c] = lds64(sbase + 3 * STAGE_B + row * (D * 2) + (j + 8 * c) * 8);
            }
        }
        __syncwarp();
        if (lane < 2) mbar_arrive(bar_emptyk + 8 * (2 + lane));
        mbar_wait(bar_qfull, 0);
        if (threadIdx.x < D) {
            const int qchunk = threadIdx.x % 24;
            const int pchunk = qchunk < 12 ? qchunk + 12 : qchunk - 12;
            const float sgn = qchunk < 12 ? -1.f : 1.f;
            const uint4 qcs = lds128(sbase + OFF_QRAW + H * D * 2 + qchunk * 16);
            const uint4 qsn = lds128(sbase + OFF_QRAW + H * D * 2 + D * 2 + qchunk * 16);
            const uint32_t cc[4] = {qcs.x, qcs.y, qcs.z, qcs.w}, ss[4] = {qsn.x, qsn.y, qsn.z, qsn.w};
#pragma unroll
            for (int i = 0; i < 4; i++) {
                const int h = threadIdx.x / 24 + 8 * i;
                const uint4 qx = lds128(sbase + OFF_QRAW + h * D * 2 + qchunk * 16);
                const uint4 qy = lds128(sbase + OFF_QRAW + h * D * 2 + pchunk * 16);
                const uint32_t xx[4] = {qx.x, qx.y, qx.z, qx.w}, yy[4] = {qy.x, qy.y, qy.z, qy.w};
                uint32_t o[4];
#pragma unroll
                for (int e = 0; e < 4; e++) {
                    const float lo = bf_round(bf_lo(xx[e]) * bf_lo(cc[e])) + bf_round(sgn * bf_lo(yy[e]) * bf_lo(ss[e]));
                    const float hi = bf_round(bf_hi(xx[e]) * bf_hi(cc[e])) + bf_round(sgn * bf_hi(yy[e]) * bf_hi(ss[e]));
                    const __nv_bfloat162 pk = __floats2bfloat162_rn(lo, hi);
                    o[e] = *reinterpret_cast<const uint32_t*>(&pk);
                }
                *reinterpret_cast<uint4*>(smem + OFF_QR + (h * D + qchunk * 8) * 2) = make_uint4(o[0], o[1], o[2], o[3]);
            }
        }
        named_bar(1, KW * 32);

        const float lscale = 0.07216878364870322f * 1.4426950408889634f;
        for (int h = 0; h < H; h++) {
            float qf[6][4];
#pragma unroll
            for (int c = 0; c < 6; c++) {
                const uint2 qq = lds64(sbase + OFF_QR + (h * D + 4 * (j + 8 * c)) * 2);
                qf[c][0] = bf_lo(qq.x); qf[c][1] = bf_hi(qq.x); qf[c][2] = bf_lo(qq.y); qf[c][3] = bf_hi(qq.y);
            }
            float* logit_out = g_logits + (size_t)h * S + b * POS + 8 * warp + 4 * j + g;
            float mx = -INFINITY;
#pragma unroll
            for (int jj = 0; jj < 2; jj++) {
                const int slot = 2 * (h & 1) + jj;
                const uint32_t stage = sbase + slot * STAGE_B;
                float logit[2];
                mbar_wait(bar_full + 16 * slot, ((h + 1) >> 1) & 1);
                mbar_wait(bar_full + 16 * slot + 8 * (warp >> 2), ((h + 1) >> 1) & 1);
#pragma unroll
                for (int u = 0; u < 2; u++) {
                    const int P = 2 * jj + u;
                    const int r = 8 * warp + 4 * u + g;
#pragma unroll
                    for (int c = 0; c < 6; c++)
                        asm volatile("" : "+r"(cr[P][c].x), "+r"(cr[P][c].y), "+r"(sr[P][c].x), "+r"(sr[P][c].y));
                    uint4 kk[6];
#pragma unroll
                    for (int c = 0; c < 6; c++) kk[c] = lds128(stage + r * ROWB + (j + 8 * c) * 16);
                    const float ks = lds_bf16(stage + AUX_SCALE + r * 2);
                    const float kz = lds_bf16(stage + AUX_ZERO + r * 2);
                    float d0 = 0.f, d1 = 0.f;
#pragma unroll
                    for (int c = 0; c < 3; c++) {
                        const uint32_t c1[2] = {cr[P][c].x, cr[P][c].y}, c2[2] = {cr[P][c + 3].x, cr[P][c + 3].y};
                        const uint32_t s1[2] = {sr[P][c].x, sr[P][c].y}, s2[2] = {sr[P][c + 3].x, sr[P][c + 3].y};
                        const int k1[4] = {(int)kk[c].x, (int)kk[c].y, (int)kk[c].z, (int)kk[c].w};
                        const int k2[4] = {(int)kk[c + 3].x, (int)kk[c + 3].y, (int)kk[c + 3].z, (int)kk[c + 3].w};
#pragma unroll
                        for (int e = 0; e < 4; e++) {
                            const float cos1 = (e & 1) ? bf_hi(c1[e >> 1]) : bf_lo(c1[e >> 1]);
                            const float cos2 = (e & 1) ? bf_hi(c2[e >> 1]) : bf_lo(c2[e >> 1]);
                            const float sin1 = (e & 1) ? bf_hi(s1[e >> 1]) : bf_lo(s1[e >> 1]);
                            const float sin2 = (e & 1) ? bf_hi(s2[e >> 1]) : bf_lo(s2[e >> 1]);
                            const float w1 = fmaf(qf[c + 3][e], sin2, qf[c][e] * cos1);
                            const float w2 = fmaf(-qf[c][e], sin1, qf[c + 3][e] * cos2);
                            d0 = fmaf((float)k1[e] - kz, w1, d0);
                            d1 = fmaf((float)k2[e] - kz, w2, d1);
                        }
                    }
                    float dot = d0 + d1;
                    dot += __shfl_xor_sync(0xffffffffu, dot, 1);
                    dot += __shfl_xor_sync(0xffffffffu, dot, 2);
                    dot += __shfl_xor_sync(0xffffffffu, dot, 4);
                    logit[u] = dot * ks * lscale;
                    mx = fmaxf(mx, logit[u]);
                }
                if (j < 2) logit_out[SROWS * jj] = j == 0 ? logit[0] : logit[1];
                __syncwarp();
                if (lane == 0) mbar_arrive(bar_emptyk + 8 * slot);
            }
            const uint32_t key = __reduce_max_sync(0xffffffffu, float_key(mx));
            if (lane == 0) {
                asm volatile("red.relaxed.cta.shared.max.u32 [%0], %1;" ::"r"(sbase + OFF_HKEY + 4 * h), "r"(key) : "memory");
                asm volatile("st.release.cta.shared.u32 [%0], %1;" ::"r"(sbase + OFF_KPROG + 4 * warp), "r"(h + 1) : "memory");
            }
        }

        if (sl == NSL) return;
        const uint4* parts = g_part + (size_t)(hb * NSL + sl) * SLICE_V;
        if (warp == 6) {
            for (unsigned spins = 0; ld_acquire_cta(sbase + OFF_READY) < (unsigned)NG; spins++) {
                if (spins > SPIN_LIMIT) __trap();
                __nanosleep(500);
            }
            const size_t row0 = (size_t)hb * S + (S - PROWS) + 4 * lane;
            float4 lg[PROWS / POS];
            uint2 sc[PROWS / POS], zr[PROWS / POS];
#pragma unroll
            for (int c = 0; c < PROWS / POS; c++) {
                lg[c] = __ldcg(reinterpret_cast<const float4*>(g_logits + row0 + c * POS));
                sc[c] = __ldg(reinterpret_cast<const uint2*>(v_scales + row0 + c * POS));
                zr[c] = __ldg(reinterpret_cast<const uint2*>(v_zeros + row0 + c * POS));
            }
            const float M = __uint_as_float(lds32(sbase + OFF_HMAX + 4 * hb));
            float lp = 0.f;
#pragma unroll
            for (int c = 0; c < PROWS / POS; c++) {
                const float p0 = ex2(lg[c].x - M), p1 = ex2(lg[c].y - M), p2 = ex2(lg[c].z - M), p3 = ex2(lg[c].w - M);
                lp += (p0 + p1) + (p2 + p3);
                float4* pw = reinterpret_cast<float4*>(smem + OFF_PW + (c * POS + 4 * lane) * 8);
                pw[0] = make_float4(p0 * bf_lo(sc[c].x), bf_lo(zr[c].x), p1 * bf_hi(sc[c].x), bf_hi(zr[c].x));
                pw[1] = make_float4(p2 * bf_lo(sc[c].y), bf_lo(zr[c].y), p3 * bf_hi(sc[c].y), bf_hi(zr[c].y));
            }
#pragma unroll
            for (int o = 16; o > 0; o >>= 1) lp += __shfl_xor_sync(0xffffffffu, lp, o);
            if (lane == 0) *reinterpret_cast<float*>(smem + OFF_PL) = lp;
        }
        named_bar(1, KW * 32);
        if (warp < 6) {
            mbar_wait(bar_near, 0);
            const float4 sum = collect<(NB + 11) / 12>(parts, 12, 2 * warp + (lane >> 4), NB, lane, 500);
            if (lane < 16) *reinterpret_cast<float4*>(smem + OFF_PRE + warp * 256 + lane * 16) = sum;
            asm volatile("bar.arrive 3, 256;" ::: "memory");
            const int t = threadIdx.x;
            float acc[4] = {0.f, 0.f, 0.f, 0.f};
            auto add_row = [&](uint4 v, uint2 pz) {
                const float pv = __uint_as_float(pz.x), vz = __uint_as_float(pz.y);
                acc[0] = fmaf((float)(int)v.x - vz, pv, acc[0]);
                acc[1] = fmaf((float)(int)v.y - vz, pv, acc[1]);
                acc[2] = fmaf((float)(int)v.z - vz, pv, acc[2]);
                acc[3] = fmaf((float)(int)v.w - vz, pv, acc[3]);
            };
            const uint32_t weights = sbase + OFF_PW + (t / 16) * 8, red = sbase + OFF_RED + t * 16;
            const int* last_src = qv + ((size_t)hb * S + (S - PREG * PBOX) + t / 16) * D + sl * PCOLS + (t % 16) * 4;
            asm volatile("createpolicy.fractional.L2::evict_first.b64 %0, 1.0;" : "=l"(pol));
            mbar_wait(bar_end, 0);
            const uint32_t slot0 = lds32(sbase + OFF_PL + 4), t_due = lds32(sbase + OFF_PL + 8), t_step = lds32(sbase + OFF_PL + 12);
            auto add_box = [&](int i) {
                uint2 pz[PU];
#pragma unroll
                for (int u = 0; u < PU; u++) pz[u] = lds64(weights + (i * PBOX + 12 * u) * 8);
                const uint32_t src = sbase + ((slot0 + i / BPS) & 3) * STAGE_B + (i % BPS) * PBOX_B + t * 16;
                mbar_wait(bar_priv + 8 * i, 0);
#pragma unroll
                for (int u = 0; u < PU; u++) add_row(lds128(src + u * (192 * 16)), pz[u]);
            };
#pragma unroll 1
            for (int i = 0; i < PEARLY; i++) add_box(i);
            uint4 last[PREG][PU];
#pragma unroll
            for (int i = 0; i < PREG; i++) {
                while ((int)(clock32() - (t_due + i * t_step)) < 0) __nanosleep(40);
#pragma unroll
                for (int u = 0; u < PU; u++)
                    asm volatile("ld.global.nc.L1::no_allocate.L2::cache_hint.v4.u32 {%0, %1, %2, %3}, [%4], %5;"
                                 : "=r"(last[i][u].x), "=r"(last[i][u].y), "=r"(last[i][u].z), "=r"(last[i][u].w)
                                 : "l"(last_src + (i * PBOX + u * 12) * D), "l"(pol));
                if (i < PREG - 1) add_box(PEARLY + i);
            }
            uint2 last_pz[PREG][PU];
#pragma unroll
            for (int i = 0; i < PREG; i++)
#pragma unroll
                for (int u = 0; u < PU; u++) last_pz[i][u] = lds64(weights + ((PSUB + i) * PBOX + 12 * u) * 8);
#pragma unroll 1
            for (int i = PEARLY + PREG - 1; i < PSUB; i++) add_box(i);
#pragma unroll
            for (int i = 0; i < PREG; i++)
#pragma unroll
                for (int u = 0; u < PU; u++) add_row(last[i][u], last_pz[i][u]);
            asm volatile("st.shared.v4.f32 [%0], {%1, %2, %3, %4};" ::"r"(red), "f"(acc[0]), "f"(acc[1]), "f"(acc[2]), "f"(acc[3]) : "memory");
            asm volatile("bar.arrive 2, 224;" ::: "memory");
        } else if (warp == 6) {
            mbar_wait(bar_end, 0);
            const float4 sum = collect<(NE - NB + 1) / 2>(parts, 2, NB + (lane >> 4), NE, lane, 200);
            if (lane < 16) *reinterpret_cast<float4*>(smem + OFF_PRE + warp * 256 + lane * 16) = sum;
            mbar_wait(bar_priv, 0);
            const uint2* sums = reinterpret_cast<const uint2*>(parts + NPART * PART_V) + lane;
            uint2 w = make_uint2(0, 0);
            for (unsigned spins = 0;; spins++) {
                const uint32_t ok = (w.x | (2 * lane >= NPART)) & (w.y | (2 * lane + 1 >= NPART)) & 1;
                if (__all_sync(0xffffffffu, ok)) break;
                if (!ok) asm volatile("ld.relaxed.gpu.global.v2.u32 {%0, %1}, [%2];" : "=r"(w.x), "=r"(w.y) : "l"(sums) : "memory");
                if (spins > SPIN_LIMIT) __trap();
            }
            float l = __uint_as_float(w.x & ~1u) + __uint_as_float(w.y & ~1u);
#pragma unroll
            for (int o = 16; o > 0; o >>= 1) l += __shfl_xor_sync(0xffffffffu, l, o);
            if (lane == 0) *reinterpret_cast<float*>(smem + OFF_PL) += l;
            asm volatile("bar.arrive 3, 256;" ::: "memory");
        } else {
            mbar_wait(bar_priv, 0);
            float4 sum = collect<(NPART - NE + 1) / 2>(parts, 2, NE + (lane >> 4), NPART, lane, 0);
            named_bar(3, 256);
#pragma unroll
            for (int w = 0; w < 7; w++) {
                const uint4 v = lds128(sbase + OFF_PRE + w * 256 + (lane & 15) * 16);
                sum.x += __uint_as_float(v.x); sum.y += __uint_as_float(v.y);
                sum.z += __uint_as_float(v.z); sum.w += __uint_as_float(v.w);
            }
            const float inv = __frcp_rn(__uint_as_float(lds32(sbase + OFF_PL)));
            const float lo0 = __shfl_sync(0xffffffffu, sum.x, lane >> 1), lo1 = __shfl_sync(0xffffffffu, sum.y, lane >> 1);
            const float hi0 = __shfl_sync(0xffffffffu, sum.z, lane >> 1), hi1 = __shfl_sync(0xffffffffu, sum.w, lane >> 1);
            float x = (lane & 1) ? hi0 : lo0, y = (lane & 1) ? hi1 : lo1;
            __nv_bfloat16* dst = out + hb * D + sl * PCOLS + 2 * lane;
            asm volatile("st.shared.v4.u32 [%0], {%1, %2, %3, %4};"
                         ::"r"(sbase + OFF_PRE + lane * 16), "r"(__float_as_uint(x)), "r"(__float_as_uint(y)),
                           "r"(__float_as_uint(inv)), "r"((uint32_t)(reinterpret_cast<uintptr_t>(dst) >> 16)) : "memory");
            named_bar(2, 224);
            float sx[4] = {x, 0.f, 0.f, 0.f}, sy[4] = {y, 0.f, 0.f, 0.f};
#pragma unroll
            for (int r = 0; r < 12; r++) {
                const uint2 v = lds64(sbase + OFF_RED + r * 256 + lane * 8);
                sx[r & 3] += __uint_as_float(v.x);
                sy[r & 3] += __uint_as_float(v.y);
            }
            x = ((sx[0] + sx[1]) + (sx[2] + sx[3])) * inv;
            y = ((sy[0] + sy[1]) + (sy[2] + sy[3])) * inv;
            *reinterpret_cast<__nv_bfloat162*>(dst) = __floats2bfloat162_rn(x, y);
        }
    } else {
        asm volatile("setmaxnreg.dec.sync.aligned.u32 88;");
        if (warp < KW + VW) {
            const int wv = warp - KW;
            const int g = lane >> 3, j = lane & 7;
            const uint32_t pvbuf = sbase + OFF_PV + wv * SROWS * 8;
            const int dst_off = (wv >> 1) * SLICE_V + (wv & 1) * 8 + j;
            int n = 0;
            while (true) {
                mbar_wait(bar_auxv + 8 * (n & 3), (n >> 2) & 1);
                const uint32_t item = lds32(sbase + (n & 3) * STAGE_B + AUX_ITEM);
                if (item & ITEM_END) break;
                const int h = item & (H - 1);
                const int last = n + (item >> 16) - 1;
                const float M = __uint_as_float(lds32(sbase + OFF_HMAX + 4 * h));
                float l = 0.f;
                float acc[4] = {0.f, 0.f, 0.f, 0.f};
#pragma unroll 1
                while (true) {
                    const int slot = n & 3;
                    const uint32_t stage = sbase + slot * STAGE_B;
#pragma unroll
                    for (int u = 0; u < 2; u++) {
                        const int r = 32 * u + lane;
                        const float p = ex2(__uint_as_float(lds32(stage + AUX_LOGIT + r * 4)) - M);
                        const float vs = lds_bf16(stage + AUX_SCALE + r * 2);
                        const float vz = lds_bf16(stage + AUX_ZERO + r * 2);
                        l += p;
                        asm volatile("st.shared.v2.f32 [%0], {%1,%2};" ::"r"(pvbuf + r * 8), "f"(p * vs), "f"(vz) : "memory");
                    }
                    if (n == last && wv == 0) {
#pragma unroll
                        for (int o = 16; o > 0; o >>= 1) l += __shfl_xor_sync(0xffffffffu, l, o);
                    }
                    __syncwarp();
#pragma unroll
                    for (int u = 0; u < 16; u++) {
                        if (u % 8 == 0) mbar_wait(bar_fullv + 16 * slot + u, (n >> 2) & 1);
                        const int r = 4 * u + g;
                        const uint2 pz = lds64(pvbuf + r * 8);
                        const uint4 v = lds128(stage + r * ROWB + wv * 128 + j * 16);
                        const float pv = __uint_as_float(pz.x), vz = __uint_as_float(pz.y);
                        acc[0] = fmaf((float)(int)v.x - vz, pv, acc[0]);
                        acc[1] = fmaf((float)(int)v.y - vz, pv, acc[1]);
                        acc[2] = fmaf((float)(int)v.z - vz, pv, acc[2]);
                        acc[3] = fmaf((float)(int)v.w - vz, pv, acc[3]);
                    }
                    __syncwarp();
                    if (lane == 0) mbar_arrive(bar_emptyv + 8 * slot);
                    if (n++ == last) break;
                    mbar_wait(bar_auxv + 8 * (n & 3), (n >> 2) & 1);
                }
#pragma unroll
                for (int e = 0; e < 4; e++) {
                    acc[e] += __shfl_xor_sync(0xffffffffu, acc[e], 8);
                    acc[e] += __shfl_xor_sync(0xffffffffu, acc[e], 16);
                }
                const int part = (item >> 8) & 255;
                uint4* dst = g_part + (size_t)h * NSL * SLICE_V;
                if (lane < 8)
                    st_relaxed(dst + part * PART_V + dst_off,
                               make_uint4(__float_as_uint(acc[0]) | 1, __float_as_uint(acc[1]) | 1, __float_as_uint(acc[2]) | 1,
                                          __float_as_uint(acc[3]) | 1));
                if (wv == 0 && lane < NSL)
                    asm volatile("st.relaxed.gpu.global.u32 [%0], %1;"
                                 ::"l"(reinterpret_cast<uint32_t*>(dst + lane * SLICE_V + NPART * PART_V) + part),
                                   "r"(__float_as_uint(l) | 1) : "memory");
            }
        } else if (warp == PRODUCER) {
            if (lane == 0) {
                const uint32_t t_start = clock32();
#pragma unroll 1
                for (int i = 1; i < 2 * KSTAGES; i++) {
                    const int n = i >> 1, p = i & 1;
                    const uint32_t stage = sbase + (n & 3) * STAGE_B, bar = bar_full + 8 * (i & 7);
                    const size_t row0 = (size_t)(n >> 1) * S + b * POS + (n & 1) * SROWS;
                    if (p) mbar_wait(bar_full + 8 * ((i - 2) & 7), ((n + 1) >> 2) & 1);
                    else if (n >= 2) mbar_wait(bar_emptyk + 8 * (n & 3), ((n - 2) >> 2) & 1);
                    mbar_expect_tx(bar, p ? HALF_B : HALF_B + 2 * SROWS * 2);
                    bulk_g2s(stage + p * HALF_B, qk + (row0 + p * (SROWS / 2)) * D, HALF_B, bar, pol);
                    if (!p) issue_aux(stage, bar, row0, k_scales, k_zeros, pol);
                }
                asm volatile("prefetch.tensormap [%0];" ::"l"(&v_map) : "memory");
                int n = 0;
                bool was_single = false;
                uint32_t prev_idx = 0, prev_time = t_start;
                unsigned ready = 0;
                while (true) {
                    const int slot0 = n & 3;
                    const uint32_t stage0 = sbase + slot0 * STAGE_B;
                    const int depth0 = was_single ? 3 : 2;
                    if (n >= 2) mbar_wait(bar_fullv + 8 * ((2 * n - depth0) & 7), ((2 * n - depth0) >> 3) & 1);
                    const unsigned idx = atomicAdd(&g_queue, 1u);
                    const uint32_t now = clock32_after(idx);
                    if (n < NST) mbar_wait(bar_emptyk + 8 * slot0, ((KSTAGES - 2 + slot0) >> 2) & 1);
                    else mbar_wait(bar_emptyv + 8 * slot0, ((n >> 2) - 1) & 1);
                    if (idx >= (unsigned)ALL_ITEMS) {
                        if (idx == (unsigned)(ALL_ITEMS + NCTA - 1)) g_queue = 0;
                        asm volatile("st.shared.u32 [%0], %1;" ::"r"(stage0 + AUX_ITEM), "r"(ITEM_END) : "memory");
                        mbar_arrive(bar_auxv + 8 * slot0);
                        if (sl == NSL) break;
                        const uint32_t t_empty =
                            now - (uint32_t)((float)(now - prev_time) * (float)(idx - ALL_ITEMS) / (float)(idx - prev_idx));
                        const uint32_t since = min(now - t_start, 1u << 22);
                        asm volatile("st.shared.u32 [%0], %1;" ::"r"(sbase + OFF_PL + 4), "r"(slot0) : "memory");
                        asm volatile("st.shared.v2.u32 [%0], {%1, %2};" ::"r"(sbase + OFF_PL + 8),
                                     "r"(t_empty + ((PFIRST + PSUB * PSTEP) * since >> 14)), "r"(PSTEP * since >> 14) : "memory");
                        mbar_arrive(bar_end);
                        if (!was_single) mbar_arrive(bar_near);
                        if (n + 1 < NST) mbar_wait(bar_emptyk + 8 * (n + 1), ((KSTAGES - 1 + n) >> 2) & 1);
                        else mbar_wait(bar_emptyv + 8 * ((n + 1) & 3), (((n + 1) >> 2) - 1) & 1);
#pragma unroll 1
                        for (int i = 0; i < PSUB; i++) {
                            const uint32_t due = t_empty + ((PFIRST + i * PSTEP) * since >> 14);
                            while ((int)(clock32() - due) < 0) {}
                            box_g2s(sbase + ((n + i / BPS) & 3) * STAGE_B + (i % BPS) * PBOX_B, &v_map, sl * PCOLS,
                                    hb * S + (S - PROWS) + i * PBOX, bar_priv + 8 * i, pol);
                        }
                        break;
                    }
                    int h, part, unit0, ustep, nstage;
                    if (idx < (unsigned)(NB * H)) {
                        h = idx / NB; part = idx % NB; unit0 = part; ustep = NB; nstage = BIG;
                    } else if (idx < (unsigned)((NB + N4) * H)) {
                        const int k = idx - NB * H;
                        h = k / N4; part = NB + k % N4; unit0 = (BIG - 1) * NB + part; ustep = N4; nstage = 4;
                    } else if (idx < (unsigned)((NB + N4 + N2) * H)) {
                        const int k = idx - (NB + N4) * H;
                        h = k / N2; part = NB + N4 + k % N2; unit0 = BIG * NB + 4 * N4 + 2 * (k % N2); ustep = 1; nstage = 2;
                    } else {
                        const int k = idx - (NB + N4 + N2) * H;
                        h = k % H; part = NB + N4 + N2 + k / H; unit0 = (BIG - 1) * NB + 3 * N4 + N2 + part; ustep = 1; nstage = 1;
                        if (!was_single) mbar_arrive(bar_near);
                    }
                    was_single = nstage == 1;
                    prev_idx = idx;
                    prev_time = now;
                    if ((unsigned)h >= GH * ready) {
                        for (unsigned spins = 0; (unsigned)h >= GH * (ready = ld_acquire_cta(sbase + OFF_READY)); spins++)
                            if (spins > SPIN_LIMIT) __trap();
                        asm volatile("fence.proxy.async.global;" ::: "memory");
                    }
                    asm volatile("st.shared.u32 [%0], %1;" ::"r"(stage0 + AUX_ITEM), "r"((nstage << 16) | (part << 8) | h) : "memory");
                    for (int u = 0; u < nstage; u++, n++) {
                        const uint32_t stage = sbase + (n & 3) * STAGE_B;
                        const uint32_t bar = bar_fullv + 16 * (n & 3), bar_aux = bar_auxv + 8 * (n & 3);
                        const size_t row0 = (size_t)h * S + (unit0 + u * ustep) * SROWS;
                        if (u > 0) {
                            if (n < NST) mbar_wait(bar_emptyk + 8 * n, ((KSTAGES - 2 + n) >> 2) & 1);
                            else mbar_wait(bar_emptyv + 8 * (n & 3), ((n >> 2) - 1) & 1);
                        }
                        mbar_expect_tx(bar_aux, 2 * SROWS * 2 + SROWS * 4);
                        issue_aux(stage, bar_aux, row0, v_scales, v_zeros, pol);
                        bulk_g2s_nohint(stage + AUX_LOGIT, g_logits + row0, SROWS * 4, bar_aux);
#pragma unroll
                        for (int p = 0; p < 2; p++) {
                            const int before = 2 * n + p - (was_single ? 3 : 2);
                            if (before >= 0) mbar_wait(bar_fullv + 8 * (before & 7), (before >> 3) & 1);
                            mbar_expect_tx(bar + 8 * p, HALF_B);
                            bulk_g2s(stage + p * HALF_B, qv + (row0 + p * (SROWS / 2)) * D, HALF_B, bar + 8 * p, pol);
                        }
                    }
                }
            }
        } else {
            unsigned target;
            asm volatile("ld.relaxed.gpu.global.u32 %0, [%1];" : "=r"(target) : "l"(&g_kcnt[NG - 1]) : "memory");
            target = (target & ~(unsigned)(NCTA - 1)) + NCTA;
            unsigned* keys = g_key + (target / NCTA & 1) * H;
            unsigned published = 0, ready = 0;
            for (unsigned spins = 0; ready < (unsigned)NG; spins++) {
                if (spins > SPIN_LIMIT) __trap();
                const unsigned done = __reduce_min_sync(0xffffffffu, ld_acquire_cta(sbase + OFF_KPROG + 4 * (lane & 7))) / GH;
                if (done > published) {
                    if (published == 0) {
                        uint4* parts = g_part + (size_t)(hb * NSL + sl) * SLICE_V;
                        if (sl < NSL)
                            for (int i = lane; i < SLICE_V; i += 32) st_relaxed(parts + i, make_uint4(0, 0, 0, 0));
                        if (b == 0) g_key[(~target / NCTA & 1) * H + lane] = 0;
                    }
                    if (lane >= GH * published && lane < GH * done)
                        asm volatile("red.relaxed.gpu.global.max.u32 [%0], %1;" ::"l"(keys + lane), "r"(lds32(sbase + OFF_HKEY + 4 * lane)) : "memory");
                    asm volatile("fence.acq_rel.gpu;" ::: "memory");
                    __syncwarp();
                    if (lane >= published && lane < done)
                        asm volatile("red.relaxed.gpu.global.add.u32 [%0], 1;" ::"l"(&g_kcnt[lane]) : "memory");
                    published = done;
                } else if (ready < published && (published == (unsigned)NG || (spins & 15) == 0)) {
                    if ((int)(ld_acquire_gpu(&g_kcnt[ready]) - target) >= 0) {
                        if (lane / GH == ready) {
                            uint32_t key;
                            asm volatile("ld.relaxed.gpu.global.u32 %0, [%1];" : "=r"(key) : "l"(keys + lane) : "memory");
                            *reinterpret_cast<float*>(smem + OFF_HMAX + 4 * lane) = key_float(key);
                        }
                        __syncwarp();
                        ready++;
                        if (lane == 0) asm volatile("st.release.cta.shared.u32 [%0], %1;" ::"r"(sbase + OFF_READY), "r"(ready) : "memory");
                    } else {
                        __nanosleep(1000);
                    }
                } else {
                    __nanosleep(100);
                }
            }
        }
    }
}

}

extern "C" void kernel_launch(void* const* d_in, const int* in_sizes, int n_in, void* d_out, int out_size) {
    (void)in_sizes; (void)n_in; (void)out_size;
    static bool configured = false;
    static decltype(&cuTensorMapEncodeTiled) encode = nullptr;
    if (!configured) {
        cudaFuncSetAttribute(kv_decode_kernel, cudaFuncAttributeMaxDynamicSharedMemorySize, SMEM_B);
        cudaDriverEntryPointQueryResult st;
        cudaGetDriverEntryPoint("cuTensorMapEncodeTiled", reinterpret_cast<void**>(&encode), cudaEnableDefault, &st);
        configured = true;
    }
    CUtensorMap v_map;
    const cuuint64_t dims[2] = {(cuuint64_t)D, (cuuint64_t)H * S};
    const cuuint64_t strides[1] = {(cuuint64_t)ROWB};
    const cuuint32_t box[2] = {(cuuint32_t)PCOLS, (cuuint32_t)PBOX};
    const cuuint32_t estr[2] = {1, 1};
    encode(&v_map, CU_TENSOR_MAP_DATA_TYPE_INT32, 2, d_in[4], dims, strides, box, estr, CU_TENSOR_MAP_INTERLEAVE_NONE,
           CU_TENSOR_MAP_SWIZZLE_NONE, CU_TENSOR_MAP_L2_PROMOTION_NONE, CU_TENSOR_MAP_FLOAT_OOB_FILL_NONE);
    kv_decode_kernel<<<NCTA, NTHREADS, SMEM_B>>>(
        (const __nv_bfloat16*)d_in[9], (const __nv_bfloat16*)d_in[10],
        (const __nv_bfloat16*)d_in[0], (const int*)d_in[1], (const __nv_bfloat16*)d_in[2],
        (const __nv_bfloat16*)d_in[3], (const int*)d_in[4], (const __nv_bfloat16*)d_in[5],
        (const __nv_bfloat16*)d_in[6], (const __nv_bfloat16*)d_in[7], (const __nv_bfloat16*)d_in[8],
        (__nv_bfloat16*)d_out, v_map);
}
```

```cpp
#include <cuda_runtime.h>
#include <cuda.h>
#include <cuda_bf16.h>
#include <stdint.h>

namespace {

constexpr int H = 32;
constexpr int S = 16384;
constexpr int D = 192;
constexpr int NCTA = 128;
constexpr int POS = S / NCTA;
constexpr int NBLK = S / POS;
constexpr int SROWS = 64;
constexpr int ROWB = D * 4;
constexpr int DATA_B = SROWS * ROWB;
constexpr int HALF_B = DATA_B / 2;
constexpr int AUX_SCALE = DATA_B;
constexpr int AUX_ZERO = AUX_SCALE + SROWS * 2;
constexpr int AUX_LOGIT = AUX_ZERO + SROWS * 2;
constexpr int AUX_ITEM = AUX_LOGIT + SROWS * 4;
constexpr int STAGE_B = AUX_ITEM + 128;
constexpr int NST = 4;
constexpr int KSTAGES = 2 * H;

constexpr int PROWS = 384;
constexpr int NSL = 3;
constexpr int PCOLS = D / NSL;
constexpr int PBOX = 48;
constexpr int PU = PBOX / 12;
constexpr int PREG = 2;
constexpr int PSUB = PROWS / PBOX - PREG;
constexpr int PEARLY = 2;
constexpr int PBOX_B = PBOX * PCOLS * 4;
constexpr int BPS = DATA_B / PBOX_B;
constexpr int PFIRST = 95, PSTEP = 25;

constexpr int BIG = 10, NB = 21, N4 = 5, N1 = 12;
constexpr int N2 = ((S - PROWS) / SROWS - BIG * NB - 4 * N4 - N1) / 2;
constexpr int NPART = NB + N4 + N2 + N1;
constexpr int NE = NPART - 8;
constexpr int ALL_ITEMS = NPART * H;
constexpr int PART_V = PCOLS / 4;
constexpr int SLICE_V = (NPART + 1) * PART_V;
constexpr uint32_t ITEM_END = 1u << 31;
static_assert(N2 > 0 && BIG * NB + 4 * N4 + 2 * N2 + N1 == (S - PROWS) / SROWS && BIG < 16, "item classes");

constexpr int GH = 8;
constexpr int NG = H / GH;
constexpr int KW = 8;
constexpr int VW = 6;
constexpr int PRODUCER = KW + VW;
constexpr int NTHREADS = 512;

constexpr int OFF_QR = NST * STAGE_B;
constexpr int OFF_PV = OFF_QR + H * D * 2;
constexpr int OFF_QRAW = OFF_PV + VW * SROWS * 8;
constexpr int QRAW_B = H * D * 2 + 2 * D * 2;
constexpr int OFF_PW = OFF_QRAW;
constexpr int OFF_RED = OFF_PW + PROWS * 4;
constexpr int OFF_PRE = OFF_RED + 192 * 16;
constexpr int OFF_PL = OFF_PRE + 7 * 256;
constexpr int OFF_PT = OFF_PL + 8;
constexpr int OFF_HKEY = OFF_QRAW + QRAW_B;
constexpr int OFF_HMAX = OFF_HKEY + H * 4;
constexpr int OFF_KPROG = OFF_HMAX + H * 4;
constexpr int OFF_READY = OFF_KPROG + 32;
constexpr int OFF_BAR = OFF_READY + 16;
constexpr int SMEM_B = OFF_BAR + (31 + PSUB) * 8;
static_assert(OFF_PT + 12 <= OFF_HKEY && PSUB <= 2 * BPS && PEARLY + PREG - 1 <= PSUB, "private rows");
static_assert(PBOX % 12 == 0 && PROWS % PBOX == 0 && PROWS % POS == 0 && PART_V == 16 && NPART <= PCOLS, "private rows");
static_assert(SMEM_B <= 232448, "shared memory budget");
static_assert(STAGE_B % 128 == 0, "stage alignment");
static_assert(NCTA == (NSL + 1) * H, "owners of the output slices");
static_assert(NCTA == NBLK, "one position block per CTA in the K phase");
static_assert((NCTA & (NCTA - 1)) == 0, "progress counter windows");
static_assert(POS * D * 2 == DATA_B, "cos/sin tiles are staged through ring slots");

constexpr unsigned SPIN_LIMIT = 1u << 23;

__device__ __align__(256) float g_logits[H * S];
__device__ __align__(256) uint4 g_part[H * NSL * SLICE_V];
__device__ __align__(128) unsigned g_key[2 * H];
__device__ __align__(128) unsigned g_kcnt[NG];
__device__ __align__(128) unsigned g_queue;

__device__ __forceinline__ uint32_t smem_u32(const void* p) { return (uint32_t)__cvta_generic_to_shared(p); }
__device__ __forceinline__ void mbar_init(uint32_t bar, uint32_t cnt) {
    asm volatile("mbarrier.init.shared::cta.b64 [%0], %1;" ::"r"(bar), "r"(cnt) : "memory");
}
__device__ __forceinline__ void mbar_expect_tx(uint32_t bar, uint32_t bytes) {
    asm volatile("mbarrier.arrive.expect_tx.shared::cta.b64 _, [%0], %1;" ::"r"(bar), "r"(bytes) : "memory");
}
__device__ __forceinline__ void mbar_arrive(uint32_t bar) {
    asm volatile("mbarrier.arrive.shared::cta.b64 _, [%0];" ::"r"(bar) : "memory");
}
__device__ __forceinline__ void mbar_wait(uint32_t bar, uint32_t parity) {
    uint32_t done;
    unsigned spins = 0;
    do {
        asm volatile(
            "{\n.reg .pred p;\n"
            "mbarrier.try_wait.parity.shared::cta.b64 p, [%1], %2;\n"
            "selp.u32 %0, 1, 0, p;\n}"
            : "=r"(done)
            : "r"(bar), "r"(parity)
            : "memory");
        if (++spins > SPIN_LIMIT) __trap();
    } while (!done);
}
__device__ __forceinline__ void bulk_g2s(uint32_t dst, const void* src, uint32_t bytes, uint32_t bar, uint64_t pol) {
    asm volatile(
        "cp.async.bulk.shared::cluster.global.mbarrier::complete_tx::bytes.L2::cache_hint [%0], [%1], %2, [%3], %4;"
        ::"r"(dst), "l"(src), "r"(bytes), "r"(bar), "l"(pol)
        : "memory");
}
__device__ __forceinline__ void bulk_g2s_nohint(uint32_t dst, const void* src, uint32_t bytes, uint32_t bar) {
    asm volatile("cp.async.bulk.shared::cluster.global.mbarrier::complete_tx::bytes [%0], [%1], %2, [%3];"
                 ::"r"(dst), "l"(src), "r"(bytes), "r"(bar)
                 : "memory");
}
__device__ __forceinline__ void box_g2s(uint32_t dst, const CUtensorMap* map, int col, int row, uint32_t bar, uint64_t pol) {
    asm volatile(
        "cp.async.bulk.tensor.2d.shared::cluster.global.mbarrier::complete_tx::bytes.L2::cache_hint [%0], [%1, {%2, %3}], [%4], %5;"
        ::"r"(dst), "l"(map), "r"(col), "r"(row), "r"(bar), "l"(pol)
        : "memory");
}
__device__ __forceinline__ void st_relaxed(uint4* p, uint4 v) {
    asm volatile("st.relaxed.gpu.global.v4.u32 [%0], {%1, %2, %3, %4};" ::"l"(p), "r"(v.x), "r"(v.y), "r"(v.z), "r"(v.w) : "memory");
}
__device__ __forceinline__ void ld_relaxed_if(uint4& r, const uint4* p, bool cond) {
    asm volatile("{\n.reg .pred p;\nsetp.ne.u32 p, %5, 0;\n@p ld.relaxed.gpu.global.v4.u32 {%0, %1, %2, %3}, [%4];\n}"
                 : "+r"(r.x), "+r"(r.y), "+r"(r.z), "+r"(r.w) : "l"(p), "r"((unsigned)cond) : "memory");
}
__device__ __forceinline__ unsigned ld_acquire_cta(uint32_t addr) {
    unsigned v;
    asm volatile("ld.acquire.cta.shared.u32 %0, [%1];" : "=r"(v) : "r"(addr) : "memory");
    return v;
}
__device__ __forceinline__ uint32_t float_key(float x) {
    const uint32_t u = __float_as_uint(x);
    return u ^ ((uint32_t)((int32_t)u >> 31) | 0x80000000u);
}
__device__ __forceinline__ float key_float(uint32_t k) {
    return __uint_as_float(k ^ ((uint32_t)((int32_t)~k >> 31) | 0x80000000u));
}
template <int N>
__device__ __forceinline__ float4 collect(const uint4* base, int stride, int first, int count, int lane, unsigned pause) {
    uint4 r[N];
#pragma unroll
    for (int i = 0; i < N; i++) {
        const uint32_t init = first + i * stride < count ? 0u : 1u;
        r[i] = make_uint4(init, init, init, init);
    }
    for (unsigned spins = 0;; spins++) {
#pragma unroll
        for (int i = 0; i < N; i++)
            ld_relaxed_if(r[i], base + (first + i * stride) * PART_V + (lane & 15), !(r[i].x & r[i].y & r[i].z & r[i].w & 1));
        uint32_t ok = 1;
#pragma unroll
        for (int i = 0; i < N; i++) ok &= r[i].x & r[i].y & r[i].z & r[i].w;
        if (__all_sync(0xffffffffu, ok & 1)) break;
        if (spins > SPIN_LIMIT) __trap();
        if (pause) __nanosleep(pause);
    }
    float4 sum = make_float4(0.f, 0.f, 0.f, 0.f);
#pragma unroll
    for (int i = 0; i < N; i++) {
        sum.x += __uint_as_float(r[i].x & ~1u); sum.y += __uint_as_float(r[i].y & ~1u);
        sum.z += __uint_as_float(r[i].z & ~1u); sum.w += __uint_as_float(r[i].w & ~1u);
    }
    sum.x += __shfl_xor_sync(0xffffffffu, sum.x, 16); sum.y += __shfl_xor_sync(0xffffffffu, sum.y, 16);
    sum.z += __shfl_xor_sync(0xffffffffu, sum.z, 16); sum.w += __shfl_xor_sync(0xffffffffu, sum.w, 16);
    return sum;
}
__device__ __forceinline__ unsigned ld_acquire_gpu(const unsigned* p) {
    unsigned v;
    asm volatile("ld.acquire.gpu.global.u32 %0, [%1];" : "=r"(v) : "l"(p) : "memory");
    return v;
}
__device__ __forceinline__ uint4 lds128(uint32_t addr) {
    uint4 v;
    asm volatile("ld.shared.v4.u32 {%0,%1,%2,%3}, [%4];" : "=r"(v.x), "=r"(v.y), "=r"(v.z), "=r"(v.w) : "r"(addr));
    return v;
}
__device__ __forceinline__ uint2 lds64(uint32_t addr) {
    uint2 v;
    asm volatile("ld.shared.v2.u32 {%0,%1}, [%2];" : "=r"(v.x), "=r"(v.y) : "r"(addr));
    return v;
}
__device__ __forceinline__ uint32_t lds32(uint32_t addr) {
    uint32_t v;
    asm volatile("ld.shared.u32 %0, [%1];" : "=r"(v) : "r"(addr));
    return v;
}
__device__ __forceinline__ float lds_bf16(uint32_t addr) {
    unsigned short v;
    asm volatile("ld.shared.u16 %0, [%1];" : "=h"(v) : "r"(addr));
    return __uint_as_float((uint32_t)v << 16);
}
__device__ __forceinline__ float bf_lo(uint32_t x) { return __uint_as_float(x << 16); }
__device__ __forceinline__ float bf_hi(uint32_t x) { return __uint_as_float(x & 0xffff0000u); }
__device__ __forceinline__ float bf_round(float x) { return __bfloat162float(__float2bfloat16_rn(x)); }
__device__ __forceinline__ float ex2(float x) {
    float y;
    asm("ex2.approx.ftz.f32 %0, %1;" : "=f"(y) : "f"(x));
    return y;
}
__device__ __forceinline__ uint32_t clock32() {
    uint32_t c;
    asm volatile("mov.u32 %0, %clock;" : "=r"(c) :: "memory");
    return c;
}
__device__ __forceinline__ uint32_t clock32_after(uint32_t x) {
    uint32_t c;
    asm volatile("{\n.reg .pred p;\nsetp.eq.u32 p, %1, 0xffffffff;\n@p mov.u32 %0, %clock_hi;\n@!p mov.u32 %0, %clock;\n}"
                 : "=r"(c) : "r"(x) : "memory");
    return c;
}
__device__ __forceinline__ void named_bar(int id, int nthreads) {
    asm volatile("bar.sync %0, %1;" ::"r"(id), "r"(nthreads) : "memory");
}

__device__ __forceinline__ void issue_aux(uint32_t dst, uint32_t bar, size_t row0, const __nv_bfloat16* scales,
                                          const __nv_bfloat16* zeros, uint64_t pol) {
    bulk_g2s(dst + AUX_SCALE, scales + row0, SROWS * 2, bar, pol);
    bulk_g2s(dst + AUX_ZERO, zeros + row0, SROWS * 2, bar, pol);
}

__global__ void __launch_bounds__(NTHREADS, 1)
kv_decode_kernel(const __nv_bfloat16* __restrict__ k_cos, const __nv_bfloat16* __restrict__ k_sin,
                 const __nv_bfloat16* __restrict__ q, const int* __restrict__ qk,
                 const __nv_bfloat16* __restrict__ k_scales, const __nv_bfloat16* __restrict__ k_zeros,
                 const int* __restrict__ qv, const __nv_bfloat16* __restrict__ v_scales,
                 const __nv_bfloat16* __restrict__ v_zeros, const __nv_bfloat16* __restrict__ q_cos,
                 const __nv_bfloat16* __restrict__ q_sin, __nv_bfloat16* __restrict__ out,
                 const __grid_constant__ CUtensorMap v_map) {
    asm volatile("{\n.reg .pred p;\n.reg .u64 a;\n.reg .u32 t, c;\nmov.u32 t, %tid.x;\nmov.u32 c, %ctaid.x;\n"
                 "mad.wide.u32 a, c, %1, %0;\nmad.wide.u32 a, t, 128, a;\nsetp.lt.u32 p, t, 256;\n"
                 "@p prefetch.global.L2 [a];\n}"
                 ::"l"(k_cos), "n"(DATA_B) : "memory");
    extern __shared__ __align__(128) unsigned char smem[];
    const uint32_t sbase = smem_u32(smem);
    const uint32_t bar_full = sbase + OFF_BAR;
    const uint32_t bar_fullv = bar_full + 8 * 8;
    const uint32_t bar_auxv = bar_fullv + 8 * 8;
    const uint32_t bar_emptyk = bar_auxv + 4 * 8;
    const uint32_t bar_emptyv = bar_emptyk + 4 * 8;
    const uint32_t bar_qfull = bar_emptyv + 4 * 8;
    const uint32_t bar_near = bar_qfull + 8;
    const uint32_t bar_end = bar_near + 8;
    const uint32_t bar_priv = bar_end + 8;

    const int warp = threadIdx.x >> 5;
    const int lane = threadIdx.x & 31;
    const int b = blockIdx.x;
    const int hb = b >> 2, sl = b & 3;

    uint64_t pol = 0;
    if (threadIdx.x == PRODUCER * 32) {
        asm volatile("createpolicy.fractional.L2::evict_first.b64 %0, 1.0;" : "=l"(pol));
        const size_t row0 = (size_t)b * POS;
        mbar_init(bar_full + 8 * 4, 1);
        mbar_init(bar_full + 8 * 5, 1);
        asm volatile("fence.proxy.async.shared::cta;" ::: "memory");
#pragma unroll
        for (int p = 0; p < 2; p++) {
            mbar_expect_tx(bar_full + 8 * (4 + p), HALF_B);
            bulk_g2s(sbase + 2 * STAGE_B + p * HALF_B, k_cos + (row0 + p * (POS / 2)) * D, HALF_B, bar_full + 8 * (4 + p), pol);
        }
#pragma unroll
        for (int p = 0; p < 2; p++) {
            mbar_init(bar_full + 8 * (6 + p), 1);
            mbar_init(bar_full + 8 * p, 1);
            mbar_init(bar_full + 8 * (2 + p), 1);
        }
        mbar_init(bar_qfull, 1);
        asm volatile("fence.proxy.async.shared::cta;" ::: "memory");
#pragma unroll
        for (int p = 0; p < 2; p++) {
            mbar_expect_tx(bar_full + 8 * (6 + p), HALF_B);
            bulk_g2s(sbase + 3 * STAGE_B + p * HALF_B, k_sin + (row0 + p * (POS / 2)) * D, HALF_B, bar_full + 8 * (6 + p), pol);
        }
        mbar_expect_tx(bar_qfull, QRAW_B);
        bulk_g2s_nohint(sbase + OFF_QRAW, q, H * D * 2, bar_qfull);
        bulk_g2s_nohint(sbase + OFF_QRAW + H * D * 2, q_cos, D * 2, bar_qfull);
        bulk_g2s_nohint(sbase + OFF_QRAW + H * D * 2 + D * 2, q_sin, D * 2, bar_qfull);
        mbar_expect_tx(bar_full, HALF_B + 2 * SROWS * 2);
        bulk_g2s(sbase, qk + row0 * D, HALF_B, bar_full, pol);
        issue_aux(sbase, bar_full, row0, k_scales, k_zeros, pol);
        for (int s = 0; s < NST; s++) {
            mbar_init(bar_fullv + 16 * s, 1);
            mbar_init(bar_fullv + 16 * s + 8, 1);
            mbar_init(bar_auxv + 8 * s, 1);
            mbar_init(bar_emptyk + 8 * s, KW);
            mbar_init(bar_emptyv + 8 * s, VW);
        }
        mbar_init(bar_near, 1);
        mbar_init(bar_end, 1);
        for (int i = 0; i < PSUB; i++) {
            mbar_init(bar_priv + 8 * i, 1);
            mbar_expect_tx(bar_priv + 8 * i, PBOX_B);
        }
    }
    if (threadIdx.x < (OFF_BAR - OFF_HKEY) / 4)
        asm volatile("st.shared.u32 [%0], %1;" ::"r"(sbase + OFF_HKEY + 4 * threadIdx.x), "r"(0) : "memory");
    __syncthreads();

    if (warp < KW) {
        asm volatile("setmaxnreg.inc.sync.aligned.u32 168;");
        const int g = lane >> 3, j = lane & 7;

        uint2 cr[4][6], sr[4][6];
#pragma unroll
        for (int p = 4; p < 8; p++) mbar_wait(bar_full + 8 * p, 0);
#pragma unroll
        for (int P = 0; P < 4; P++) {
            const int row = SROWS * (P >> 1) + 8 * warp + 4 * (P & 1) + g;
#pragma unroll
            for (int c = 0; c < 6; c++) {
                cr[P][c] = lds64(sbase + 2 * STAGE_B + row * (D * 2) + (j + 8 * c) * 8);
                sr[P][c] = lds64(sbase + 3 * STAGE_B + row * (D * 2) + (j + 8 * c) * 8);
            }
        }
        __syncwarp();
        if (lane < 2) mbar_arrive(bar_emptyk + 8 * (2 + lane));
        mbar_wait(bar_qfull, 0);
        if (threadIdx.x < D) {
            const int qchunk = threadIdx.x % 24;
            const int pchunk = qchunk < 12 ? qchunk + 12 : qchunk - 12;
            const float sgn = qchunk < 12 ? -1.f : 1.f;
            const uint4 qcs = lds128(sbase + OFF_QRAW + H * D * 2 + qchunk * 16);
            const uint4 qsn = lds128(sbase + OFF_QRAW + H * D * 2 + D * 2 + qchunk * 16);
            const uint32_t cc[4] = {qcs.x, qcs.y, qcs.z, qcs.w}, ss[4] = {qsn.x, qsn.y, qsn.z, qsn.w};
#pragma unroll
            for (int i = 0; i < 4; i++) {
                const int h = threadIdx.x / 24 + 8 * i;
                const uint4 qx = lds128(sbase + OFF_QRAW + h * D * 2 + qchunk * 16);
                const uint4 qy = lds128(sbase + OFF_QRAW + h * D * 2 + pchunk * 16);
                const uint32_t xx[4] = {qx.x, qx.y, qx.z, qx.w}, yy[4] = {qy.x, qy.y, qy.z, qy.w};
                uint32_t o[4];
#pragma unroll
                for (int e = 0; e < 4; e++) {
                    const float lo = bf_round(bf_lo(xx[e]) * bf_lo(cc[e])) + bf_round(sgn * bf_lo(yy[e]) * bf_lo(ss[e]));
                    const float hi = bf_round(bf_hi(xx[e]) * bf_hi(cc[e])) + bf_round(sgn * bf_hi(yy[e]) * bf_hi(ss[e]));
                    const __nv_bfloat162 pk = __floats2bfloat162_rn(lo, hi);
                    o[e] = *reinterpret_cast<const uint32_t*>(&pk);
                }
                *reinterpret_cast<uint4*>(smem + OFF_QR + (h * D + qchunk * 8) * 2) = make_uint4(o[0], o[1], o[2], o[3]);
            }
        }
        named_bar(1, KW * 32);

        const float lscale = 0.07216878364870322f * 1.4426950408889634f;
        for (int h = 0; h < H; h++) {
            float qf[6][4];
#pragma unroll
            for (int c = 0; c < 6; c++) {
                const uint2 qq = lds64(sbase + OFF_QR + (h * D + 4 * (j + 8 * c)) * 2);
                qf[c][0] = bf_lo(qq.x); qf[c][1] = bf_hi(qq.x); qf[c][2] = bf_lo(qq.y); qf[c][3] = bf_hi(qq.y);
            }
            float* logit_out = g_logits + (size_t)h * S + b * POS + 8 * warp + 4 * j + g;
            float mx = -INFINITY;
#pragma unroll
            for (int jj = 0; jj < 2; jj++) {
                const int slot = 2 * (h & 1) + jj;
                const uint32_t stage = sbase + slot * STAGE_B;
                float logit[2];
                mbar_wait(bar_full + 16 * slot, ((h + 1) >> 1) & 1);
                mbar_wait(bar_full + 16 * slot + 8 * (warp >> 2), ((h + 1) >> 1) & 1);
#pragma unroll
                for (int u = 0; u < 2; u++) {
                    const int P = 2 * jj + u;
                    const int r = 8 * warp + 4 * u + g;
#pragma unroll
                    for (int c = 0; c < 6; c++)
                        asm volatile("" : "+r"(cr[P][c].x), "+r"(cr[P][c].y), "+r"(sr[P][c].x), "+r"(sr[P][c].y));
                    uint4 kk[6];
#pragma unroll
                    for (int c = 0; c < 6; c++) kk[c] = lds128(stage + r * ROWB + (j + 8 * c) * 16);
                    const float ks = lds_bf16(stage + AUX_SCALE + r * 2);
                    const float kz = lds_bf16(stage + AUX_ZERO + r * 2);
                    float d0 = 0.f, d1 = 0.f;
#pragma unroll
                    for (int c = 0; c < 3; c++) {
                        const uint32_t c1[2] = {cr[P][c].x, cr[P][c].y}, c2[2] = {cr[P][c + 3].x, cr[P][c + 3].y};
                        const uint32_t s1[2] = {sr[P][c].x, sr[P][c].y}, s2[2] = {sr[P][c + 3].x, sr[P][c + 3].y};
                        const int k1[4] = {(int)kk[c].x, (int)kk[c].y, (int)kk[c].z, (int)kk[c].w};
                        const int k2[4] = {(int)kk[c + 3].x, (int)kk[c + 3].y, (int)kk[c + 3].z, (int)kk[c + 3].w};
#pragma unroll
                        for (int e = 0; e < 4; e++) {
                            const float cos1 = (e & 1) ? bf_hi(c1[e >> 1]) : bf_lo(c1[e >> 1]);
                            const float cos2 = (e & 1) ? bf_hi(c2[e >> 1]) : bf_lo(c2[e >> 1]);
                            const float sin1 = (e & 1) ? bf_hi(s1[e >> 1]) : bf_lo(s1[e >> 1]);
                            const float sin2 = (e & 1) ? bf_hi(s2[e >> 1]) : bf_lo(s2[e >> 1]);
                            const float w1 = fmaf(qf[c + 3][e], sin2, qf[c][e] * cos1);
                            const float w2 = fmaf(-qf[c][e], sin1, qf[c + 3][e] * cos2);
                            d0 = fmaf((float)k1[e] - kz, w1, d0);
                            d1 = fmaf((float)k2[e] - kz, w2, d1);
                        }
                    }
                    float dot = d0 + d1;
                    dot += __shfl_xor_sync(0xffffffffu, dot, 1);
                    dot += __shfl_xor_sync(0xffffffffu, dot, 2);
                    dot += __shfl_xor_sync(0xffffffffu, dot, 4);
                    logit[u] = dot * ks * lscale;
                    mx = fmaxf(mx, logit[u]);
                }
                if (j < 2) logit_out[SROWS * jj] = j == 0 ? logit[0] : logit[1];
                __syncwarp();
                if (lane == 0) mbar_arrive(bar_emptyk + 8 * slot);
            }
            const uint32_t key = __reduce_max_sync(0xffffffffu, float_key(mx));
            if (lane == 0) {
                asm volatile("red.relaxed.cta.shared.max.u32 [%0], %1;" ::"r"(sbase + OFF_HKEY + 4 * h), "r"(key) : "memory");
                asm volatile("st.release.cta.shared.u32 [%0], %1;" ::"r"(sbase + OFF_KPROG + 4 * warp), "r"(h + 1) : "memory");
            }
        }

        if (sl == NSL) return;
        const uint4* parts = g_part + (size_t)(hb * NSL + sl) * SLICE_V;
        if (warp == 6) {
            for (unsigned spins = 0; ld_acquire_cta(sbase + OFF_READY) < (unsigned)NG; spins++) {
                if (spins > SPIN_LIMIT) __trap();
                __nanosleep(500);
            }
            const size_t row0 = (size_t)hb * S + (S - PROWS) + 4 * lane;
            float4 lg[PROWS / POS];
            uint2 sc[PROWS / POS], zr[PROWS / POS];
#pragma unroll
            for (int c = 0; c < PROWS / POS; c++) {
                lg[c] = __ldcg(reinterpret_cast<const float4*>(g_logits + row0 + c * POS));
                sc[c] = __ldg(reinterpret_cast<const uint2*>(v_scales + row0 + c * POS));
                zr[c] = __ldg(reinterpret_cast<const uint2*>(v_zeros + row0 + c * POS));
            }
            const float M = __uint_as_float(lds32(sbase + OFF_HMAX + 4 * hb));
            float lp = 0.f, zp = 0.f;
#pragma unroll
            for (int c = 0; c < PROWS / POS; c++) {
                const float p0 = ex2(lg[c].x - M), p1 = ex2(lg[c].y - M), p2 = ex2(lg[c].z - M), p3 = ex2(lg[c].w - M);
                lp += (p0 + p1) + (p2 + p3);
                const float4 w = make_float4(p0 * bf_lo(sc[c].x), p1 * bf_hi(sc[c].x), p2 * bf_lo(sc[c].y), p3 * bf_hi(sc[c].y));
                zp += (w.x * bf_lo(zr[c].x) + w.y * bf_hi(zr[c].x)) + (w.z * bf_lo(zr[c].y) + w.w * bf_hi(zr[c].y));
                *reinterpret_cast<float4*>(smem + OFF_PW + (c * POS + 4 * lane) * 4) = w;
            }
#pragma unroll
            for (int o = 16; o > 0; o >>= 1) {
                lp += __shfl_xor_sync(0xffffffffu, lp, o);
                zp += __shfl_xor_sync(0xffffffffu, zp, o);
            }
            if (lane == 0) *reinterpret_cast<float2*>(smem + OFF_PL) = make_float2(lp, zp);
        }
        named_bar(1, KW * 32);
        if (warp < 6) {
            mbar_wait(bar_near, 0);
            const float4 sum = collect<(NB + 11) / 12>(parts, 12, 2 * warp + (lane >> 4), NB, lane, 500);
            if (lane < 16) *reinterpret_cast<float4*>(smem + OFF_PRE + warp * 256 + lane * 16) = sum;
            asm volatile("bar.arrive 3, 256;" ::: "memory");
            const int t = threadIdx.x;
            float acc[4] = {0.f, 0.f, 0.f, 0.f};
            auto add_row = [&](uint4 v, uint32_t w) {
                acc[0] = fmaf((float)(int)v.x, __uint_as_float(w), acc[0]);
                acc[1] = fmaf((float)(int)v.y, __uint_as_float(w), acc[1]);
                acc[2] = fmaf((float)(int)v.z, __uint_as_float(w), acc[2]);
                acc[3] = fmaf((float)(int)v.w, __uint_as_float(w), acc[3]);
            };
            const uint32_t weights = sbase + OFF_PW + (t / 16) * 4, red = sbase + OFF_RED + t * 16;
            const int* last_src = qv + ((size_t)hb * S + (S - PREG * PBOX) + t / 16) * D + sl * PCOLS + (t % 16) * 4;
            asm volatile("createpolicy.fractional.L2::evict_first.b64 %0, 1.0;" : "=l"(pol));
            mbar_wait(bar_end, 0);
            const uint32_t t_due = lds32(sbase + OFF_PT), t_step = lds32(sbase + OFF_PT + 4), slot0 = lds32(sbase + OFF_PT + 8);
            auto add_box = [&](int i) {
                uint32_t w[PU];
#pragma unroll
                for (int u = 0; u < PU; u++) w[u] = lds32(weights + (i * PBOX + 12 * u) * 4);
                const uint32_t src = sbase + ((slot0 + i / BPS) & 3) * STAGE_B + (i % BPS) * PBOX_B + t * 16;
                mbar_wait(bar_priv + 8 * i, 0);
#pragma unroll
                for (int u = 0; u < PU; u++) add_row(lds128(src + u * (192 * 16)), w[u]);
            };
#pragma unroll 1
            for (int i = 0; i < PEARLY; i++) add_box(i);
            uint4 last[PREG][PU];
#pragma unroll
            for (int i = 0; i < PREG; i++) {
                while ((int)(clock32() - (t_due + i * t_step)) < 0) __nanosleep(40);
#pragma unroll
                for (int u = 0; u < PU; u++)
                    asm volatile("ld.global.nc.L1::no_allocate.L2::cache_hint.v4.u32 {%0, %1, %2, %3}, [%4], %5;"
                                 : "=r"(last[i][u].x), "=r"(last[i][u].y), "=r"(last[i][u].z), "=r"(last[i][u].w)
                                 : "l"(last_src + (i * PBOX + u * 12) * D), "l"(pol));
                if (i < PREG - 1) add_box(PEARLY + i);
            }
            uint32_t last_w[PREG][PU];
#pragma unroll
            for (int i = 0; i < PREG; i++)
#pragma unroll
                for (int u = 0; u < PU; u++) last_w[i][u] = lds32(weights + ((PSUB + i) * PBOX + 12 * u) * 4);
#pragma unroll 1
            for (int i = PEARLY + PREG - 1; i < PSUB; i++) add_box(i);
#pragma unroll
            for (int i = 0; i < PREG; i++)
#pragma unroll
                for (int u = 0; u < PU; u++) add_row(last[i][u], last_w[i][u]);
            asm volatile("st.shared.v4.f32 [%0], {%1, %2, %3, %4};" ::"r"(red), "f"(acc[0]), "f"(acc[1]), "f"(acc[2]), "f"(acc[3]) : "memory");
            asm volatile("bar.arrive 2, 224;" ::: "memory");
        } else if (warp == 6) {
            mbar_wait(bar_end, 0);
            const float4 sum = collect<(NE - NB + 1) / 2>(parts, 2, NB + (lane >> 4), NE, lane, 200);
            if (lane < 16) *reinterpret_cast<float4*>(smem + OFF_PRE + warp * 256 + lane * 16) = sum;
            mbar_wait(bar_priv, 0);
            const uint2* sums = reinterpret_cast<const uint2*>(parts + NPART * PART_V) + lane;
            uint2 w = make_uint2(0, 0);
            for (unsigned spins = 0;; spins++) {
                const uint32_t ok = (w.x | (2 * lane >= NPART)) & (w.y | (2 * lane + 1 >= NPART)) & 1;
                if (__all_sync(0xffffffffu, ok)) break;
                if (!ok) asm volatile("ld.relaxed.gpu.global.v2.u32 {%0, %1}, [%2];" : "=r"(w.x), "=r"(w.y) : "l"(sums) : "memory");
                if (spins > SPIN_LIMIT) __trap();
            }
            float l = __uint_as_float(w.x & ~1u) + __uint_as_float(w.y & ~1u);
#pragma unroll
            for (int o = 16; o > 0; o >>= 1) l += __shfl_xor_sync(0xffffffffu, l, o);
            if (lane == 0) *reinterpret_cast<float*>(smem + OFF_PL) += l;
            asm volatile("bar.arrive 3, 256;" ::: "memory");
        } else {
            mbar_wait(bar_priv, 0);
            float4 sum = collect<(NPART - NE + 1) / 2>(parts, 2, NE + (lane >> 4), NPART, lane, 0);
            named_bar(3, 256);
#pragma unroll
            for (int w = 0; w < 7; w++) {
                const uint4 v = lds128(sbase + OFF_PRE + w * 256 + (lane & 15) * 16);
                sum.x += __uint_as_float(v.x); sum.y += __uint_as_float(v.y);
                sum.z += __uint_as_float(v.z); sum.w += __uint_as_float(v.w);
            }
            const uint2 pl = lds64(sbase + OFF_PL);
            const float inv = __frcp_rn(__uint_as_float(pl.x));
            const float lo0 = __shfl_sync(0xffffffffu, sum.x, lane >> 1), lo1 = __shfl_sync(0xffffffffu, sum.y, lane >> 1);
            const float hi0 = __shfl_sync(0xffffffffu, sum.z, lane >> 1), hi1 = __shfl_sync(0xffffffffu, sum.w, lane >> 1);
            float x = ((lane & 1) ? hi0 : lo0) - __uint_as_float(pl.y), y = ((lane & 1) ? hi1 : lo1) - __uint_as_float(pl.y);
            __nv_bfloat16* dst = out + hb * D + sl * PCOLS + 2 * lane;
            asm volatile("st.shared.v4.u32 [%0], {%1, %2, %3, %4};"
                         ::"r"(sbase + OFF_PRE + lane * 16), "r"(__float_as_uint(x)), "r"(__float_as_uint(y)),
                           "r"(__float_as_uint(inv)), "r"((uint32_t)(reinterpret_cast<uintptr_t>(dst) >> 16)) : "memory");
            named_bar(2, 224);
            uint2 v[12];
#pragma unroll
            for (int r = 0; r < 12; r++) v[r] = lds64(sbase + OFF_RED + r * 256 + lane * 8);
            float sx[4], sy[4];
#pragma unroll
            for (int r = 0; r < 4; r++) {
                sx[r] = (__uint_as_float(v[3 * r].x) + __uint_as_float(v[3 * r + 1].x)) + __uint_as_float(v[3 * r + 2].x);
                sy[r] = (__uint_as_float(v[3 * r].y) + __uint_as_float(v[3 * r + 1].y)) + __uint_as_float(v[3 * r + 2].y);
            }
            x = (((x + sx[0]) + (sx[1] + sx[2])) + sx[3]) * inv;
            y = (((y + sy[0]) + (sy[1] + sy[2])) + sy[3]) * inv;
            *reinterpret_cast<__nv_bfloat162*>(dst) = __floats2bfloat162_rn(x, y);
        }
    } else {
        asm volatile("setmaxnreg.dec.sync.aligned.u32 88;");
        if (warp < KW + VW) {
            const int wv = warp - KW;
            const int g = lane >> 3, j = lane & 7;
            const uint32_t pvbuf = sbase + OFF_PV + wv * SROWS * 8;
            const int dst_off = (wv >> 1) * SLICE_V + (wv & 1) * 8 + j;
            int n = 0;
            while (true) {
                mbar_wait(bar_auxv + 8 * (n & 3), (n >> 2) & 1);
                const uint32_t item = lds32(sbase + (n & 3) * STAGE_B + AUX_ITEM);
                if (item & ITEM_END) break;
                const int h = item & (H - 1);
                const int last = n + (item >> 16) - 1;
                const float M = __uint_as_float(lds32(sbase + OFF_HMAX + 4 * h));
                float l = 0.f;
                float acc[4] = {0.f, 0.f, 0.f, 0.f};
#pragma unroll 1
                while (true) {
                    const int slot = n & 3;
                    const uint32_t stage = sbase + slot * STAGE_B;
#pragma unroll
                    for (int u = 0; u < 2; u++) {
                        const int r = 32 * u + lane;
                        const float p = ex2(__uint_as_float(lds32(stage + AUX_LOGIT + r * 4)) - M);
                        const float vs = lds_bf16(stage + AUX_SCALE + r * 2);
                        const float vz = lds_bf16(stage + AUX_ZERO + r * 2);
                        l += p;
                        asm volatile("st.shared.v2.f32 [%0], {%1,%2};" ::"r"(pvbuf + r * 8), "f"(p * vs), "f"(vz) : "memory");
                    }
                    if (n == last && wv == 0) {
#pragma unroll
                        for (int o = 16; o > 0; o >>= 1) l += __shfl_xor_sync(0xffffffffu, l, o);
                    }
                    __syncwarp();
#pragma unroll
                    for (int u = 0; u < 16; u++) {
                        if (u % 8 == 0) mbar_wait(bar_fullv + 16 * slot + u, (n >> 2) & 1);
                        const int r = 4 * u + g;
                        const uint2 pz = lds64(pvbuf + r * 8);
                        const uint4 v = lds128(stage + r * ROWB + wv * 128 + j * 16);
                        const float pv = __uint_as_float(pz.x), vz = __uint_as_float(pz.y);
                        acc[0] = fmaf((float)(int)v.x - vz, pv, acc[0]);
                        acc[1] = fmaf((float)(int)v.y - vz, pv, acc[1]);
                        acc[2] = fmaf((float)(int)v.z - vz, pv, acc[2]);
                        acc[3] = fmaf((float)(int)v.w - vz, pv, acc[3]);
                    }
                    __syncwarp();
                    if (lane == 0) mbar_arrive(bar_emptyv + 8 * slot);
                    if (n++ == last) break;
                    mbar_wait(bar_auxv + 8 * (n & 3), (n >> 2) & 1);
                }
#pragma unroll
                for (int e = 0; e < 4; e++) {
                    acc[e] += __shfl_xor_sync(0xffffffffu, acc[e], 8);
                    acc[e] += __shfl_xor_sync(0xffffffffu, acc[e], 16);
                }
                const int part = (item >> 8) & 255;
                uint4* dst = g_part + (size_t)h * NSL * SLICE_V;
                if (lane < 8)
                    st_relaxed(dst + part * PART_V + dst_off,
                               make_uint4(__float_as_uint(acc[0]) | 1, __float_as_uint(acc[1]) | 1, __float_as_uint(acc[2]) | 1,
                                          __float_as_uint(acc[3]) | 1));
                if (wv == 0 && lane < NSL)
                    asm volatile("st.relaxed.gpu.global.u32 [%0], %1;"
                                 ::"l"(reinterpret_cast<uint32_t*>(dst + lane * SLICE_V + NPART * PART_V) + part),
                                   "r"(__float_as_uint(l) | 1) : "memory");
            }
        } else if (warp == PRODUCER) {
            if (lane == 0) {
                const uint32_t t_start = clock32();
#pragma unroll 1
                for (int i = 1; i < 2 * KSTAGES; i++) {
                    const int n = i >> 1, p = i & 1;
                    const uint32_t stage = sbase + (n & 3) * STAGE_B, bar = bar_full + 8 * (i & 7);
                    const size_t row0 = (size_t)(n >> 1) * S + b * POS + (n & 1) * SROWS;
                    if (p) mbar_wait(bar_full + 8 * ((i - 2) & 7), ((n + 1) >> 2) & 1);
                    else if (n >= 2) mbar_wait(bar_emptyk + 8 * (n & 3), ((n - 2) >> 2) & 1);
                    mbar_expect_tx(bar, p ? HALF_B : HALF_B + 2 * SROWS * 2);
                    bulk_g2s(stage + p * HALF_B, qk + (row0 + p * (SROWS / 2)) * D, HALF_B, bar, pol);
                    if (!p) issue_aux(stage, bar, row0, k_scales, k_zeros, pol);
                }
                asm volatile("prefetch.tensormap [%0];" ::"l"(&v_map) : "memory");
                int n = 0;
                bool was_single = false;
                uint32_t prev_idx = 0, prev_time = t_start;
                unsigned ready = 0;
                while (true) {
                    const int slot0 = n & 3;
                    const uint32_t stage0 = sbase + slot0 * STAGE_B;
                    const int depth0 = was_single ? 3 : 2;
                    if (n >= 2) mbar_wait(bar_fullv + 8 * ((2 * n - depth0) & 7), ((2 * n - depth0) >> 3) & 1);
                    const unsigned idx = atomicAdd(&g_queue, 1u);
                    const uint32_t now = clock32_after(idx);
                    if (n < NST) mbar_wait(bar_emptyk + 8 * slot0, ((KSTAGES - 2 + slot0) >> 2) & 1);
                    else mbar_wait(bar_emptyv + 8 * slot0, ((n >> 2) - 1) & 1);
                    if (idx >= (unsigned)ALL_ITEMS) {
                        if (idx == (unsigned)(ALL_ITEMS + NCTA - 1)) g_queue = 0;
                        asm volatile("st.shared.u32 [%0], %1;" ::"r"(stage0 + AUX_ITEM), "r"(ITEM_END) : "memory");
                        mbar_arrive(bar_auxv + 8 * slot0);
                        if (sl == NSL) break;
                        const uint32_t t_empty =
                            now - (uint32_t)((float)(now - prev_time) * (float)(idx - ALL_ITEMS) / (float)(idx - prev_idx));
                        const uint32_t since = min(now - t_start, 1u << 22);
                        asm volatile("st.shared.u32 [%0], %1;" ::"r"(sbase + OFF_PT + 8), "r"(slot0) : "memory");
                        asm volatile("st.shared.v2.u32 [%0], {%1, %2};" ::"r"(sbase + OFF_PT),
                                     "r"(t_empty + ((PFIRST + PSUB * PSTEP) * since >> 14)), "r"(PSTEP * since >> 14) : "memory");
                        mbar_arrive(bar_end);
                        if (!was_single) mbar_arrive(bar_near);
                        if (n + 1 < NST) mbar_wait(bar_emptyk + 8 * (n + 1), ((KSTAGES - 1 + n) >> 2) & 1);
                        else mbar_wait(bar_emptyv + 8 * ((n + 1) & 3), (((n + 1) >> 2) - 1) & 1);
#pragma unroll 1
                        for (int i = 0; i < PSUB; i++) {
                            const uint32_t due = t_empty + ((PFIRST + i * PSTEP) * since >> 14);
                            while ((int)(clock32() - due) < 0) {}
                            box_g2s(sbase + ((n + i / BPS) & 3) * STAGE_B + (i % BPS) * PBOX_B, &v_map, sl * PCOLS,
                                    hb * S + (S - PROWS) + i * PBOX, bar_priv + 8 * i, pol);
                        }
                        break;
                    }
                    int h, part, unit0, ustep, nstage;
                    if (idx < (unsigned)(NB * H)) {
                        h = idx / NB; part = idx % NB; unit0 = part; ustep = NB; nstage = BIG;
                    } else if (idx < (unsigned)((NB + N4) * H)) {
                        const int k = idx - NB * H;
                        h = k / N4; part = NB + k % N4; unit0 = (BIG - 1) * NB + part; ustep = N4; nstage = 4;
                    } else if (idx < (unsigned)((NB + N4 + N2) * H)) {
                        const int k = idx - (NB + N4) * H;
                        h = k / N2; part = NB + N4 + k % N2; unit0 = BIG * NB + 4 * N4 + 2 * (k % N2); ustep = 1; nstage = 2;
                    } else {
                        const int k = idx - (NB + N4 + N2) * H;
                        h = k % H; part = NB + N4 + N2 + k / H; unit0 = (BIG - 1) * NB + 3 * N4 + N2 + part; ustep = 1; nstage = 1;
                        if (!was_single) mbar_arrive(bar_near);
                    }
                    was_single = nstage == 1;
                    prev_idx = idx;
                    prev_time = now;
                    if ((unsigned)h >= GH * ready) {
                        for (unsigned spins = 0; (unsigned)h >= GH * (ready = ld_acquire_cta(sbase + OFF_READY)); spins++)
                            if (spins > SPIN_LIMIT) __trap();
                        asm volatile("fence.proxy.async.global;" ::: "memory");
                    }
                    asm volatile("st.shared.u32 [%0], %1;" ::"r"(stage0 + AUX_ITEM), "r"((nstage << 16) | (part << 8) | h) : "memory");
                    for (int u = 0; u < nstage; u++, n++) {
                        const uint32_t stage = sbase + (n & 3) * STAGE_B;
                        const uint32_t bar = bar_fullv + 16 * (n & 3), bar_aux = bar_auxv + 8 * (n & 3);
                        const size_t row0 = (size_t)h * S + (unit0 + u * ustep) * SROWS;
                        if (u > 0) {
                            if (n < NST) mbar_wait(bar_emptyk + 8 * n, ((KSTAGES - 2 + n) >> 2) & 1);
                            else mbar_wait(bar_emptyv + 8 * (n & 3), ((n >> 2) - 1) & 1);
                        }
                        mbar_expect_tx(bar_aux, 2 * SROWS * 2 + SROWS * 4);
                        issue_aux(stage, bar_aux, row0, v_scales, v_zeros, pol);
                        bulk_g2s_nohint(stage + AUX_LOGIT, g_logits + row0, SROWS * 4, bar_aux);
#pragma unroll
                        for (int p = 0; p < 2; p++) {
                            const int before = 2 * n + p - (was_single ? 3 : 2);
                            if (before >= 0) mbar_wait(bar_fullv + 8 * (before & 7), (before >> 3) & 1);
                            mbar_expect_tx(bar + 8 * p, HALF_B);
                            bulk_g2s(stage + p * HALF_B, qv + (row0 + p * (SROWS / 2)) * D, HALF_B, bar + 8 * p, pol);
                        }
                    }
                }
            }
        } else {
            unsigned target;
            asm volatile("ld.relaxed.gpu.global.u32 %0, [%1];" : "=r"(target) : "l"(&g_kcnt[NG - 1]) : "memory");
            target = (target & ~(unsigned)(NCTA - 1)) + NCTA;
            unsigned* keys = g_key + (target / NCTA & 1) * H;
            unsigned published = 0, ready = 0;
            for (unsigned spins = 0; ready < (unsigned)NG; spins++) {
                if (spins > SPIN_LIMIT) __trap();
                const unsigned done = __reduce_min_sync(0xffffffffu, ld_acquire_cta(sbase + OFF_KPROG + 4 * (lane & 7))) / GH;
                if (done > published) {
                    if (published == 0) {
                        uint4* parts = g_part + (size_t)(hb * NSL + sl) * SLICE_V;
                        if (sl < NSL)
                            for (int i = lane; i < SLICE_V; i += 32) st_relaxed(parts + i, make_uint4(0, 0, 0, 0));
                        if (b == 0) g_key[(~target / NCTA & 1) * H + lane] = 0;
                    }
                    if (lane >= GH * published && lane < GH * done)
                        asm volatile("red.relaxed.gpu.global.max.u32 [%0], %1;" ::"l"(keys + lane), "r"(lds32(sbase + OFF_HKEY + 4 * lane)) : "memory");
                    asm volatile("fence.acq_rel.gpu;" ::: "memory");
                    __syncwarp();
                    if (lane >= published && lane < done)
                        asm volatile("red.relaxed.gpu.global.add.u32 [%0], 1;" ::"l"(&g_kcnt[lane]) : "memory");
                    published = done;
                } else if (ready < published && (published == (unsigned)NG || (spins & 15) == 0)) {
                    if ((int)(ld_acquire_gpu(&g_kcnt[ready]) - target) >= 0) {
                        if (lane / GH == ready) {
                            uint32_t key;
                            asm volatile("ld.relaxed.gpu.global.u32 %0, [%1];" : "=r"(key) : "l"(keys + lane) : "memory");
                            *reinterpret_cast<float*>(smem + OFF_HMAX + 4 * lane) = key_float(key);
                        }
                        __syncwarp();
                        ready++;
                        if (lane == 0) asm volatile("st.release.cta.shared.u32 [%0], %1;" ::"r"(sbase + OFF_READY), "r"(ready) : "memory");
                    } else {
                        __nanosleep(1000);
                    }
                } else {
                    __nanosleep(100);
                }
            }
        }
    }
}

}

extern "C" void kernel_launch(void* const* d_in, const int* in_sizes, int n_in, void* d_out, int out_size) {
    (void)in_sizes; (void)n_in; (void)out_size;
    static bool configured = false;
    static decltype(&cuTensorMapEncodeTiled) encode = nullptr;
    if (!configured) {
        cudaFuncSetAttribute(kv_decode_kernel, cudaFuncAttributeMaxDynamicSharedMemorySize, SMEM_B);
        cudaDriverEntryPointQueryResult st;
        cudaGetDriverEntryPoint("cuTensorMapEncodeTiled", reinterpret_cast<void**>(&encode), cudaEnableDefault, &st);
        configured = true;
    }
    CUtensorMap v_map;
    const cuuint64_t dims[2] = {(cuuint64_t)D, (cuuint64_t)H * S};
    const cuuint64_t strides[1] = {(cuuint64_t)ROWB};
    const cuuint32_t box[2] = {(cuuint32_t)PCOLS, (cuuint32_t)PBOX};
    const cuuint32_t estr[2] = {1, 1};
    encode(&v_map, CU_TENSOR_MAP_DATA_TYPE_INT32, 2, d_in[4], dims, strides, box, estr, CU_TENSOR_MAP_INTERLEAVE_NONE,
           CU_TENSOR_MAP_SWIZZLE_NONE, CU_TENSOR_MAP_L2_PROMOTION_NONE, CU_TENSOR_MAP_FLOAT_OOB_FILL_NONE);
    kv_decode_kernel<<<NCTA, NTHREADS, SMEM_B>>>(
        (const __nv_bfloat16*)d_in[9], (const __nv_bfloat16*)d_in[10],
        (const __nv_bfloat16*)d_in[0], (const int*)d_in[1], (const __nv_bfloat16*)d_in[2],
        (const __nv_bfloat16*)d_in[3], (const int*)d_in[4], (const __nv_bfloat16*)d_in[5],
        (const __nv_bfloat16*)d_in[6], (const __nv_bfloat16*)d_in[7], (const __nv_bfloat16*)d_in[8],
        (__nv_bfloat16*)d_out, v_map);
}
```
